```python
import torch

def _softmax(x, axis=-1):
    return torch.softmax(x, dim=axis)
def _gelu(x):
    return torch.nn.functional.gelu(x, approximate="tanh")
def _silu(x):
    return torch.nn.functional.silu(x)
def _sigmoid(x):
    return torch.sigmoid(x)
def _layernorm(x, axis=-1, eps=1e-5):
    m = x.mean(dim=axis, keepdim=True)
    v = x.var(dim=axis, keepdim=True, unbiased=False)
    return (x - m) / torch.sqrt(v + eps)
def _scatter_add(tgt, idx, src, axis=0):
    return tgt.clone().index_add_(axis, idx, src)
def _segment_sum(src, seg, n):
    out = torch.zeros((n,) + src.shape[1:], dtype=src.dtype)
    return out.index_add_(0, seg, src)
def _pad(x, pw):
    flat = tuple(v for pair in reversed(pw) for v in pair)
    return torch.nn.functional.pad(x, flat)

kernel_name = 'parallel_sum__sliding_block_cached__geglu_ffn__decode'

def setup_inputs():

    _w = (lambda a: (lambda t: t.to(torch.bfloat16) if t.is_floating_point() else t)(torch.as_tensor(a)))
    def _A_setup():
        B, Sq, D = 1, 1, 576
        Hq, Hkv, Sk, Dh = 32, 16, 65536, 128
        assert Hq % Hkv == 0, (Hq, Hkv)
        return {
            "x": _w((lambda *s: torch.randn(*s, dtype=torch.bfloat16) * 0.05)(B, Sq, D)),
            "k_cache": _w((lambda *s: torch.randn(*s, dtype=torch.bfloat16) * 3.2)(B, Hkv, Sk, Dh)),
            "v_cache": _w((lambda *s: torch.randn(*s, dtype=torch.bfloat16) * 1.6)(B, Hkv, Sk, Dh)),
            "wq": _w((lambda *s: torch.randn(*s, dtype=torch.bfloat16) * 3.2)(D, Hq * Dh) * (D ** -0.5)),
            "wo": _w((lambda *s: torch.randn(*s, dtype=torch.bfloat16) * 1.6)(Hq * Dh, D) * ((Hq * Dh) ** -0.5)),
        }
    _A_in = _A_setup()

    def _B_setup():
        B, S, D, F = 1, 1, 576, 4608
        return {
            "x": _w((lambda *s: torch.randn(*s, dtype=torch.bfloat16) * 0.05)(B, S, D)),
            "w_gate": _w((lambda *s: torch.randn(*s, dtype=torch.bfloat16) * 0.05)(D, F)),
            "w_up": _w((lambda *s: torch.randn(*s, dtype=torch.bfloat16) * 0.05)(D, F)),
            "w_down": _w((lambda *s: torch.randn(*s, dtype=torch.bfloat16) * 0.05)(F, D)),
        }
    _B_in = _B_setup()

    return {
        "A_x": _A_in["x"],
        "A_k_cache": _A_in["k_cache"],
        "A_v_cache": _A_in["v_cache"],
        "A_wq": _A_in["wq"],
        "A_wo": _A_in["wo"],
        "B_x": _B_in["x"],
        "B_w_gate": _B_in["w_gate"],
        "B_w_up": _B_in["w_up"],
        "B_w_down": _B_in["w_down"],
    }

def reference(A_x, A_k_cache, A_v_cache, A_wq, A_wo, B_x, B_w_gate, B_w_up, B_w_down):
    def _A_ref(x, k_cache, v_cache, wq, wo):
        B, Sq, D = x.shape
        Hq, Dh = 32, 128
        Hkv, Sk = k_cache.shape[1], k_cache.shape[2]
        W = min(4096, max(256, Sk // 4))
        rep = Hq // Hkv
        q = (lambda x, *d: x.permute(*d))((x @ wq).reshape(B, Sq, Hq, Dh), 0, 2, 1, 3)
        k = (lambda x, n, axis: torch.repeat_interleave(x, n, dim=axis))(k_cache[:, :, Sk - W:, :], rep, axis=1)
        v = (lambda x, n, axis: torch.repeat_interleave(x, n, dim=axis))(v_cache[:, :, Sk - W:, :], rep, axis=1)
        scores = torch.einsum("bhqd,bhkd->bhqk", q, k) * (Dh ** -0.5)
        p = _softmax(scores, axis=-1)
        o = torch.einsum("bhqk,bhkd->bhqd", p, v)
        return (lambda x, *d: x.permute(*d))(o, 0, 2, 1, 3).reshape(B, Sq, Hq * Dh) @ wo

    def _B_ref(x, w_gate, w_up, w_down):
        return (_gelu(x @ w_gate) * (x @ w_up)) @ w_down

    x = A_x
    xn = _layernorm(x, axis=-1)
    return x + _A_ref(xn, A_k_cache, A_v_cache, A_wq, A_wo) + _B_ref(xn, B_w_gate, B_w_up, B_w_down)
```

```cpp
#include <cuda_runtime.h>
#include <cuda_bf16.h>
#include <cuda.h>
#include <stdint.h>
#include <stddef.h>

namespace {

constexpr int D_MODEL = 576;
constexpr int SK = 65536;
constexpr int WIN = 4096;
constexpr int NCTA = 128;

#define QTIMER 2
#define POLL_SLEEP 200
#define INFLIGHT 3
#define INFLIGHT2 INFLIGHT
#define INFLIGHT3 3
#define WIN_AT1 10
#define WIN_AT2 21
#define OTIMER 1
constexpr int NFIRST = INFLIGHT;
constexpr int T_K = 3;
constexpr int T_V = 11;
constexpr int T_GU = 19;
constexpr int T_W = 23;
constexpr int NTILE = 27;

constexpr int KV_BYTES = 16384;
constexpr int KV_WRAP = 13 * KV_BYTES;
constexpr int WQ_BYTES = 48 * 256;
constexpr int G_BYTES = 144 * 80;
constexpr int WO_BYTES = 32 * 288, WD_BYTES = 36 * 288;
constexpr int SM_WQ = 11 * KV_BYTES;
constexpr int SM_GU = 3 * KV_BYTES;
constexpr int SM_W = SM_GU + 8 * G_BYTES;
constexpr int SM_END = SM_W + 4 * (WO_BYTES + WD_BYTES);

constexpr int NMMA_WARPS = 9;
constexpr int NGATHER_WARPS = 4;
constexpr int NTHREADS = (NMMA_WARPS + NGATHER_WARPS + 1) * 32;
constexpr int P_PITCH = 520;

struct Maps {
    CUtensorMap wq, k, v, wg, wu, wo, wd;
};

constexpr int DEP_X = 0, DEP_O = 1, DEP_H = 2, DEP_Q = 3, DEP_P = 4, REL_WQ = 5, REL_K = 6, REL_V = 7, DEP_GU = 8;
struct SmemMisc {
    unsigned long long full[NTILE];
    unsigned long long dep[19];
    __nv_bfloat16 xn[576];
    __nv_bfloat16 o[32];
    __nv_bfloat16 h[48];
    __nv_bfloat16 q[256];
    __nv_bfloat16 s[2 * 512];
    __nv_bfloat16 p[4 * P_PITCH];
    float red[9 * 40 * 2];
    float wmax[16];
    float wsum[16];
};
constexpr int SMEM_BYTES = SM_END + (int)sizeof(SmemMisc) + 1024;
static_assert(SMEM_BYTES <= 232448, "smem");

constexpr int OFF_Q = 0;
constexpr int OFF_O = NCTA * 64;
constexpr int OFF_ML = OFF_O + 32 * 8 * 64;
constexpr int NREC = OFF_ML + 256;
#define ACC_STRIDE 1
struct Scratch {
    uint4 rec[NREC];
    float4 acc[288 * ACC_STRIDE];
    unsigned epoch[NCTA];
};
__device__ __align__(128) Scratch g_scratch;

#define TRACE_PT(i) do { } while (0)
#define CLK_PT(i) do { } while (0)

constexpr unsigned SPIN_LIMIT = 1u << 24;

__device__ __forceinline__ uint32_t smem_u32(const void* p) { return (uint32_t)__cvta_generic_to_shared(p); }
__device__ __forceinline__ void mbar_init(uint32_t bar, int cnt) {
    asm volatile("mbarrier.init.shared::cta.b64 [%0], %1;" ::"r"(bar), "r"(cnt) : "memory");
}
__device__ __forceinline__ void mbar_expect_tx(uint32_t bar, uint32_t bytes) {
    asm volatile("mbarrier.arrive.expect_tx.shared::cta.b64 _, [%0], %1;" ::"r"(bar), "r"(bytes) : "memory");
}
__device__ __forceinline__ void mbar_arrive(uint32_t bar) {
    asm volatile("mbarrier.arrive.shared::cta.b64 _, [%0];" ::"r"(bar) : "memory");
}
__device__ __forceinline__ void mbar_wait0(uint32_t bar) {
    unsigned it = 0;
    while (true) {
        uint32_t ok;
        asm volatile(
            "{\n.reg .pred p;\n"
            "mbarrier.try_wait.parity.shared::cta.b64 p, [%1], 0;\n"
            "selp.u32 %0, 1, 0, p;\n}"
            : "=r"(ok) : "r"(bar) : "memory");
        if (ok) break;
        if (++it > SPIN_LIMIT) __trap();
    }
}
__device__ __forceinline__ void tma3d(uint32_t dst, const CUtensorMap* m, int c0, int c1, int c2, uint32_t bar) {
    asm volatile(
        "cp.async.bulk.tensor.3d.shared::cluster.global.mbarrier::complete_tx::bytes [%0], [%1, {%3, %4, %5}], [%2];"
        ::"r"(dst), "l"(m), "r"(bar), "r"(c0), "r"(c1), "r"(c2) : "memory");
}
__device__ __forceinline__ void ldsm4(uint32_t (&r)[4], uint32_t addr) {
    asm volatile("ldmatrix.sync.aligned.m8n8.x4.shared.b16 {%0,%1,%2,%3}, [%4];"
                 : "=r"(r[0]), "=r"(r[1]), "=r"(r[2]), "=r"(r[3]) : "r"(addr) : "memory");
}
__device__ __forceinline__ void ldsm4t(uint32_t (&r)[4], uint32_t addr) {
    asm volatile("ldmatrix.sync.aligned.m8n8.x4.trans.shared.b16 {%0,%1,%2,%3}, [%4];"
                 : "=r"(r[0]), "=r"(r[1]), "=r"(r[2]), "=r"(r[3]) : "r"(addr) : "memory");
}
__device__ __forceinline__ void mma16816(float (&c)[4], const uint32_t (&a)[4], uint32_t b0, uint32_t b1) {
    asm volatile(
        "mma.sync.aligned.m16n8k16.row.col.f32.bf16.bf16.f32 {%0,%1,%2,%3}, {%4,%5,%6,%7}, {%8,%9}, {%0,%1,%2,%3};"
        : "+f"(c[0]), "+f"(c[1]), "+f"(c[2]), "+f"(c[3])
        : "r"(a[0]), "r"(a[1]), "r"(a[2]), "r"(a[3]), "r"(b0), "r"(b1));
}
__device__ __forceinline__ void bar_sync(int id, int n) { asm volatile("bar.sync %0, %1;" ::"r"(id), "r"(n) : "memory"); }

__device__ __forceinline__ unsigned long long pack64(uint32_t lo, uint32_t hi) {
    return ((unsigned long long)hi << 32) | lo;
}
__device__ __forceinline__ void st_rec2(uint4* p, float v0, float v1, uint32_t tag) {
    asm volatile("st.relaxed.gpu.global.v2.b64 [%0], {%1, %2};" ::"l"(p), "l"(pack64(__float_as_uint(v0), tag)),
                 "l"(pack64(__float_as_uint(v1), tag)) : "memory");
}
__device__ __forceinline__ uint4 ld_rec2(const uint4* p) {
    unsigned long long a, b;
    asm volatile("ld.relaxed.gpu.global.v2.b64 {%0, %1}, [%2];" : "=l"(a), "=l"(b) : "l"(p) : "memory");
    return make_uint4((uint32_t)a, (uint32_t)(a >> 32), (uint32_t)b, (uint32_t)(b >> 32));
}
__device__ __forceinline__ float bf16r(float x) { return __bfloat162float(__float2bfloat16_rn(x)); }
__device__ __forceinline__ float bf_lo(uint32_t u) { return __uint_as_float(u << 16); }
__device__ __forceinline__ float bf_hi(uint32_t u) { return __uint_as_float(u & 0xffff0000u); }
__device__ __forceinline__ uint32_t pack_bf(float lo, float hi) {
    __nv_bfloat162 v = __floats2bfloat162_rn(lo, hi);
    return *reinterpret_cast<uint32_t*>(&v);
}
__device__ __forceinline__ uint32_t lds32(uint32_t a) {
    uint32_t v;
    asm volatile("ld.shared.b32 %0, [%1];" : "=r"(v) : "r"(a) : "memory");
    return v;
}
__device__ __forceinline__ float2 lds64f(uint32_t a) {
    float2 v;
    asm volatile("ld.shared.v2.f32 {%0, %1}, [%2];" : "=f"(v.x), "=f"(v.y) : "r"(a) : "memory");
    return v;
}
__device__ __forceinline__ void sts32(uint32_t a, uint32_t v) { asm volatile("st.shared.b32 [%0], %1;" ::"r"(a), "r"(v) : "memory"); }
__device__ __forceinline__ void sts64f(uint32_t a, float x, float y) {
    asm volatile("st.shared.v2.f32 [%0], {%1, %2};" ::"r"(a), "f"(x), "f"(y) : "memory");
}
__device__ __forceinline__ void sts_bf16(uint32_t a, float v) {
    asm volatile("{\n.reg .b16 h;\ncvt.rn.bf16.f32 h, %1;\nst.shared.b16 [%0], h;\n}" ::"r"(a), "f"(v) : "memory");
}
__device__ __forceinline__ float ex2(float x) {
    float y;
    asm("ex2.approx.ftz.f32 %0, %1;" : "=f"(y) : "f"(x));
    return y;
}
__device__ __forceinline__ float shx(float v, int m) { return __shfl_xor_sync(0xffffffffu, v, m); }
constexpr float L2E = 1.4426950408889634f;
#define MISC(f) (misc + (uint32_t)offsetof(SmemMisc, f))

__global__ void __launch_bounds__(NTHREADS, 1)
fused_decode_kernel(const __nv_bfloat16* __restrict__ x, __nv_bfloat16* __restrict__ out, Scratch* __restrict__ scr,
                    const __grid_constant__ Maps maps) {
    uint4* const g_rec = scr->rec;
    float4* const g_acc = scr->acc;
    unsigned* const g_epoch = scr->epoch;
    extern __shared__ unsigned char smem_raw[];
    const uint32_t smem_base = (smem_u32(smem_raw) + 1023u) & ~1023u;
    const uint32_t misc = smem_base + SM_END;
    const uint32_t full0 = MISC(full);
    const uint32_t dep0 = MISC(dep);

    const int tid = threadIdx.x;
    const int b = blockIdx.x;
    const int q4 = b >> 2, r4 = b & 3;
    const int g8 = b >> 3, s8 = b & 7;

    if (tid >= 32) {
    const int warp = __shfl_sync(0xffffffffu, tid >> 5, 0);
    const int lane = tid & 31;
    uint32_t tag, xs[9];
    if (warp == 1) {
#pragma unroll
        for (int j = 0; j < 9; j++)
            asm volatile("ld.global.nc.u32 %0, [%1];" : "=r"(xs[j]) : "l"(reinterpret_cast<const uint32_t*>(x) + lane + 32 * j));
    }
    asm volatile("ld.relaxed.gpu.global.u32 %0, [%1];" : "=r"(tag) : "l"(&g_epoch[b]) : "memory");
    if (lane == 0) {
#pragma unroll
        for (int j = 0; j < 3; j++) {
            const int i = NFIRST - 3 + warp * 3 + j;
            mbar_init(full0 + 8 * i, (i < NTILE + DEP_H) ? 1 : (i == NTILE + DEP_H) ? 2 : (i == NTILE + DEP_Q) ? 4 : (i == NTILE + DEP_GU) ? 9 : 8);
        }
        asm volatile("fence.mbarrier_init.release.cluster;" ::: "memory");
    }
    __syncthreads();

    if (warp <= NGATHER_WARPS) {
        if (warp == 1) {
            float s = 0.f;
#pragma unroll
            for (int j = 0; j < 9; j++) s += bf_lo(xs[j]) + bf_hi(xs[j]);
#pragma unroll
            for (int off = 16; off >= 1; off >>= 1) s += shx(s, off);
            const float mean = s * (1.0f / D_MODEL);
            float v = 0.f;
#pragma unroll
            for (int j = 0; j < 9; j++) {
                float d0 = bf_lo(xs[j]) - mean, d1 = bf_hi(xs[j]) - mean;
                v += d0 * d0 + d1 * d1;
            }
#pragma unroll
            for (int off = 16; off >= 1; off >>= 1) v += shx(v, off);
            const float mb = bf16r(mean);
            float den;
            asm("sqrt.approx.f32 %0, %1;" : "=f"(den) : "f"(bf16r(bf16r(v * (1.0f / D_MODEL)) + 1e-5f)));
            const float inv = __fdividef(1.0f, bf16r(den));
#pragma unroll
            for (int j = 0; j < 9; j++)
                sts32(MISC(xn) + (lane + 32 * j) * 4, pack_bf(bf16r(bf_lo(xs[j]) - mb) * inv, bf16r(bf_hi(xs[j]) - mb) * inv));
            __syncwarp();
            if (lane == 0) mbar_arrive(dep0 + 8 * DEP_X);
            if (lane == 0) TRACE_PT(1);
        }
        const int gt = tid - 32;
        const int gw = warp - 1;

        float w0 = 0.f, w1 = 0.f, w2 = 0.f, w3 = 0.f;
#pragma unroll 1
        for (uint32_t prog = (0x0943'0C92'0C91'0BA9ull >> (16 * gw)) & 0xffff; prog; prog >>= 4) {
            const bool live = prog & 8;
            const int step = prog & 7;
            if (live) asm volatile("or.b32 %0, %0, 0x80000000;" : "+r"(tag));
            if (step == 4) {
                if (live) mbar_wait0(dep0 + 8 * DEP_GU);
                const int j = (gw & 2) * 16 + lane;
                const uint32_t ra = MISC(red) + (min(j, 35) + ((b & 1) << 2)) * 8;
                float g = 0.f, u = 0.f;
#pragma unroll
                for (int w = 0; w < 9; w++) {
                    const float2 t = lds64f(ra + w * 320);
                    g += t.x;
                    u += t.y;
                }
                g = bf16r(g);
                const float k = -2.0f * 0.7978845608028654f * L2E;
                const float hv = bf16r(__fdividef(g, 1.0f + ex2(k * (g + 0.044715f * g * g * g)))) * bf16r(u);
                if (live && j < 48) sts_bf16(MISC(h) + j * 2, j < 36 ? hv : 0.f);
                __syncwarp();
                if (live && lane == 0) mbar_arrive(dep0 + 8 * DEP_H);
                if (live && gt == 32) TRACE_PT(5);
                continue;
            }
            uint4 r0 = make_uint4(0, 0, 0, 0), r1 = r0, r2 = r0, r3 = r0;
            {
                int idx, stride;
                uint32_t wbar;
                if (step == 1) { idx = OFF_Q + (g8 * 8 + (gt >> 6) * 4) * 64 + (gt & 63); stride = 64; wbar = full0 + 8 * (T_K + QTIMER); }
                else if (step == 2) { idx = OFF_ML + (g8 * 8 + (lane & 1) * 4) * 2 + (q4 & 1); stride = 2; wbar = full0 + 8 * (T_V + 6); }
                else { idx = OFF_O + (q4 * 8 + (lane & 1) * 4) * 64 + r4 * 16 + (lane >> 1); stride = 64; wbar = full0 + 8 * (T_GU + OTIMER); }
                const uint32_t want = live ? tag : 0u;
                if (live) mbar_wait0(wbar);
                if (live && gt == 0) TRACE_PT(15 + step);
                const uint4* src = g_rec + idx;
                unsigned it = 0;
                while (true) {
                    if (r0.y != want || r0.w != want) r0 = ld_rec2(src);
                    if (r1.y != want || r1.w != want) r1 = ld_rec2(src + stride);
                    if (r2.y != want || r2.w != want) r2 = ld_rec2(src + 2 * stride);
                    if (r3.y != want || r3.w != want) r3 = ld_rec2(src + 3 * stride);
                    const uint32_t bad = ((r0.y ^ want) | (r0.w ^ want) | (r1.y ^ want)) | ((r1.w ^ want) | (r2.y ^ want) | (r2.w ^ want)) |
                                         ((r3.y ^ want) | (r3.w ^ want));
                    if (bad == 0) break;
                    if (++it > SPIN_LIMIT) __trap();
                }
                __syncwarp();
            }
            const float a0 = __uint_as_float(r0.x), a1 = __uint_as_float(r1.x), a2 = __uint_as_float(r2.x), a3 = __uint_as_float(r3.x);
            const float b0 = __uint_as_float(r0.z), b1 = __uint_as_float(r1.z), b2 = __uint_as_float(r2.z), b3 = __uint_as_float(r3.z);
            if (step == 2) {
                float mx = fmaxf(fmaxf(a0, a1), fmaxf(a2, a3));
                mx = fmaxf(mx, shx(mx, 1));
                w0 = ex2((a0 - mx) * L2E); w1 = ex2((a1 - mx) * L2E); w2 = ex2((a2 - mx) * L2E); w3 = ex2((a3 - mx) * L2E);
                float L = w0 * b0 + w1 * b1 + w2 * b2 + w3 * b3;
                L += shx(L, 1);
                const float inv = __fdividef(1.0f, L);
                w0 *= inv; w1 *= inv; w2 *= inv; w3 *= inv;
            } else if (step == 3) {
                const float u = w0 * a0 + w1 * a1 + w2 * a2 + w3 * a3;
                const float v = w0 * b0 + w1 * b1 + w2 * b2 + w3 * b3;
                const float tot = ((lane & 1) ? v : u) + shx((lane & 1) ? u : v, 1);
                if (live) sts_bf16(MISC(o) + ((lane & 16) + ((lane >> 1) & 7) + (lane & 1) * 8) * 2, tot);
                __syncwarp();
                if (live && lane == 0) mbar_arrive(dep0 + 8 * DEP_O);
                if (live && gt == 0) TRACE_PT(8);
            } else {
                const float u = (a0 + a1) + (a2 + a3), v = (b0 + b1) + (b2 + b3);
                const uint32_t qa = MISC(q) + ((gt >> 3) * 16 + (gt & 7)) * 2;
                if (live) {
                    sts_bf16(qa, u);
                    sts_bf16(qa + 16, v);
                }
                __syncwarp();
                if (live && lane == 0) mbar_arrive(dep0 + 8 * DEP_Q);
                if (live && gt == 0) TRACE_PT(4);
            }
        }
        return;
    }

    const int mw = warp - 1 - NGATHER_WARPS;
    const int gq = lane >> 2, t4 = lane & 3;
    const int lrow = (lane & 7) + ((lane >> 4) << 3);
    const int lchk = (lane >> 3) & 1;
    const int pidx = mw * 8 + gq;
    const int ocol = t4 * 144 + mw * 16 + gq;
    const float xres0 = __bfloat162float(x[ocol]), xres1 = __bfloat162float(x[ocol + 8]);
    uint4* const rec_o = g_rec + OFF_O + ((g8 * 2 + (t4 & 1)) * 8 + s8) * 64 + pidx;

#pragma unroll 1
    for (int it0 = -1; it0 < 6; it0++) {
        const bool live = it0 >= 0;
        if (live) asm volatile("or.b32 %0, %0, 0x80000000;" : "+r"(tag));
        int sec = live ? it0 : (mw >= 7 ? 0 : mw);
        if (live && mw == 8 && sec < 4) {
            if (sec != 3) continue;
            sec = 6;
        }
        if (sec == 0 || sec == 3) {
            const bool ph = sec;
            int tile = ph ? T_V : 0;
            const int tend = !live ? tile + 1 : ph ? T_GU : T_K;
            const uint32_t a_off = smem_base + lrow * 128 + ((((mw & 3) * 2 + lchk) ^ (lane & 7)) << 4) + ((mw & 4) ? (ph ? 8192 : 6144) : 0);
            int taddr = ph ? 8 * KV_BYTES : SM_WQ;
            uint32_t baddr = t4 * 4 + (ph ? MISC(p) + (gq & 3) * (P_PITCH * 2) : MISC(xn) + r4 * 288);
            if (live) mbar_wait0(dep0 + 8 * (ph ? DEP_P : DEP_X));
            float c0[4] = {0.f, 0.f, 0.f, 0.f}, c1[4] = {0.f, 0.f, 0.f, 0.f};
#pragma unroll 1
            for (; tile < tend; tile++) {
                const uint32_t base = a_off + taddr;
                taddr += ph ? KV_BYTES : WQ_BYTES;
                if (taddr >= KV_WRAP) taddr -= KV_WRAP;
                uint32_t bf[8];
#pragma unroll
                for (int j = 0; j < 8; j++) bf[j] = lds32(baddr + j * 16);
                baddr += ph ? 128 : 96;
                if (live) mbar_wait0(full0 + 8 * tile);
                uint32_t a0[4], a1[4], a2[4], a3[4];
                ldsm4t(a0, base);
                ldsm4t(a1, base + 2048);
                ldsm4t(a2, base + 4096);
                if (ph) ldsm4t(a3, base + 6144);
                mma16816(c0, a0, bf[0], bf[1]);
                mma16816(c1, a1, bf[2], bf[3]);
                mma16816(c0, a2, bf[4], bf[5]);
                if (ph) mma16816(c1, a3, bf[6], bf[7]);
                __syncwarp();
                if ((tile == T_V + 4 || tile == T_K - 1) && lane == 0) mbar_arrive(dep0 + 8 * (ph ? REL_V : REL_WQ));
            }
            float v0 = c0[0] + c1[0], v1 = c0[2] + c1[2];
            if (ph) { v0 += c0[1] + c1[1]; v1 += c0[3] + c1[3]; }
            if (live && t4 <= (int)ph) st_rec2(ph ? rec_o : g_rec + OFF_Q + b * 64 + pidx, v0, v1, tag);
            if (live && tid == 160) TRACE_PT(ph ? 7 : 2);
        } else if (sec == 1) {
            if (live) mbar_wait0(dep0 + 8 * DEP_Q);
            uint32_t qb[16];
#pragma unroll
            for (int j = 0; j < 16; j++) qb[j] = lds32(MISC(q) + (gq & 1) * 256 + t4 * 4 + j * 16);
            const int krow = (mw & 3) * 16 + (lane & 15);
            float m = -INFINITY;
#pragma unroll 1
            for (int i = live ? 0 : 3; i < 4; i++) {
                const int kt = (mw >> 2) + 2 * i;
                const uint32_t base = smem_base + kt * KV_BYTES + krow * 128;
                if (live) mbar_wait0(full0 + 8 * (T_K + kt));
                float c0[4] = {0.f, 0.f, 0.f, 0.f}, c1[4] = {0.f, 0.f, 0.f, 0.f};
#pragma unroll
                for (int ks = 0; ks < 4; ks++) {
                    uint32_t a0[4], a1[4];
                    const uint32_t sw = ((ks * 2 + (lane >> 4)) ^ (lane & 7)) << 4;
                    ldsm4(a0, base + sw);
                    ldsm4(a1, base + 8192 + sw);
                    mma16816(c0, a0, qb[2 * ks], qb[2 * ks + 1]);
                    mma16816(c1, a1, qb[8 + 2 * ks], qb[8 + 2 * ks + 1]);
                }
                __syncwarp();
                if (i == 1 && lane == 0) mbar_arrive(dep0 + 8 * REL_K);
                const float lo = (t4 & 1) ? c0[1] + c1[1] : c0[0] + c1[0];
                const float hi = (t4 & 1) ? c0[3] + c1[3] : c0[2] + c1[2];
                const float sc = bf16r(bf16r((t4 & 2) ? hi : lo) * 0.08838834764831845f);
                m = fmaxf(m, sc);
                sts_bf16(MISC(s) + ((t4 & 1) * 512 + kt * 64 + (mw & 3) * 16 + gq + (t4 & 2) * 4) * 2, sc);
            }
#pragma unroll
            for (int off = 2; off <= 16; off <<= 1) m = fmaxf(m, shx(m, off));
            if (lane < 2) sts32(MISC(wmax) + mw * 8 + lane * 4, __float_as_uint(m));
            if (live && t4 < 2) st_rec2(rec_o, 0.f, 0.f, 0u);
        } else if (sec == 2) {
            if (live) bar_sync(1, 256);
            float m0 = -INFINITY, m1 = -INFINITY;
#pragma unroll
            for (int j = 0; j < 8; j++) {
                m0 = fmaxf(m0, __uint_as_float(lds32(MISC(wmax) + j * 8)));
                m1 = fmaxf(m1, __uint_as_float(lds32(MISC(wmax) + j * 8 + 4)));
            }
            const int kp = mw * 32 + lane;
            const uint32_t s0 = lds32(MISC(s) + kp * 4);
            const uint32_t s1 = lds32(MISC(s) + 1024 + kp * 4);
            const float p00 = ex2((bf_lo(s0) - m0) * L2E), p01 = ex2((bf_hi(s0) - m0) * L2E);
            const float p10 = ex2((bf_lo(s1) - m1) * L2E), p11 = ex2((bf_hi(s1) - m1) * L2E);
            const uint32_t h0 = pack_bf(p00, p01), h1 = pack_bf(p10, p11);
            const uint32_t pa = MISC(p) + kp * 4;
            sts32(pa, h0);
            sts32(pa + P_PITCH * 2, pack_bf(p00 - bf_lo(h0), p01 - bf_hi(h0)));
            sts32(pa + P_PITCH * 4, h1);
            sts32(pa + P_PITCH * 6, pack_bf(p10 - bf_lo(h1), p11 - bf_hi(h1)));
            const float l0 = p00 + p01, l1 = p10 + p11;
            float l = ((lane & 1) ? l1 : l0) + shx((lane & 1) ? l0 : l1, 1);
#pragma unroll
            for (int off = 2; off <= 16; off <<= 1) l += shx(l, off);
            if (lane < 2) sts32(MISC(wsum) + mw * 8 + lane * 4, __float_as_uint(l));
            __syncwarp();
            if (live && lane == 0) mbar_arrive(dep0 + 8 * DEP_P);
            if (live && tid == 160) TRACE_PT(6);
        } else if (sec == 6) {
            if (live) mbar_wait0(dep0 + 8 * DEP_P);
            float m = -INFINITY, l = 0.f;
#pragma unroll
            for (int j = 0; j < 8; j++) {
                m = fmaxf(m, __uint_as_float(lds32(MISC(wmax) + j * 8 + (lane & 1) * 4)));
                l += __uint_as_float(lds32(MISC(wsum) + j * 8 + (lane & 1) * 4));
            }
            if (live && lane < 2) st_rec2(g_rec + OFF_ML + (g8 * 8 + s8) * 2 + lane, m, l, tag);
            if (live && lane == 0) g_epoch[b] = tag + 1u;
        } else if (sec == 4) {
            float acc[5][4];
#pragma unroll
            for (int c = 0; c < 5; c++) acc[c][0] = acc[c][1] = acc[c][2] = acc[c][3] = 0.f;
            uint32_t base = smem_base + SM_GU + lchk * G_BYTES + (mw * 16 + lrow) * 80;
            uint32_t baddr = MISC(xn) + mw * 32 + t4 * 4;
#pragma unroll 1
            for (int i = live ? 0 : 3; i < 4; i++) {
                const uint32_t b0 = lds32(baddr), b1 = lds32(baddr + 16);
                baddr += 288;
                if (live) mbar_wait0(full0 + 8 * (T_GU + i));
                uint32_t a[5][4];
#pragma unroll
                for (int c = 0; c < 5; c++) ldsm4t(a[c], base + c * 16);
#pragma unroll
                for (int c = 0; c < 5; c++) mma16816(acc[c], a[c], b0, b1);
                base += 2 * G_BYTES;
            }
            const uint32_t red = MISC(red) + (mw * 40 + gq) * 8;
            sts64f(red + t4 * 64, t4 == 0 ? acc[0][0] : t4 == 1 ? acc[1][0] : t4 == 2 ? acc[2][0] : acc[3][0],
                   t4 == 0 ? acc[0][2] : t4 == 1 ? acc[1][2] : t4 == 2 ? acc[2][2] : acc[3][2]);
            if (t4 == 0) sts64f(red + 256, acc[4][0], acc[4][2]);
            __syncwarp();
            if (live && lane == 0) mbar_arrive(dep0 + 8 * DEP_GU);
        } else {
            const int chunk = 2 * mw + lchk;
            const uint32_t coff = smem_base + SM_W + lrow * 144 + (chunk - (chunk >= 9 ? 9 : 0)) * 16;
            const uint32_t ao = coff + (chunk >= 9 ? 32 * 144 : 0);
            const uint32_t ad = coff + WO_BYTES + (chunk >= 9 ? 36 * 144 : 0);
            const uint32_t last = (lrow < 4 ? 32 : 16) * 144;
            float4* const acc = g_acc + (t4 * 72 + pidx) * ACC_STRIDE;
            uint32_t a[4][5][4], bf[10];
            float4 old[2];
            float v0 = 0.f, v1 = 0.f;
#pragma unroll
            for (int i = 0; i < 4; i++) {
                if (live) mbar_wait0(full0 + 8 * (T_W + i));
                ldsm4t(a[i][0], ao + i * (WO_BYTES + WD_BYTES));
                ldsm4t(a[i][1], ao + i * (WO_BYTES + WD_BYTES) + 16 * 144);
                ldsm4t(a[i][2], ad + i * (WO_BYTES + WD_BYTES));
                ldsm4t(a[i][3], ad + i * (WO_BYTES + WD_BYTES) + 16 * 144);
                ldsm4t(a[i][4], ad + i * (WO_BYTES + WD_BYTES) + last);
                if (i < 2) continue;
                if (i == 2) {
                    if (live) {
                        mbar_wait0(dep0 + 8 * DEP_O);
                        mbar_wait0(dep0 + 8 * DEP_H);
                    }
                    if (live && tid == 160) TRACE_PT(9);
#pragma unroll
                    for (int j = 0; j < 10; j++) bf[j] = lds32(MISC(o) + t4 * 4 + j * 16);
                }
#pragma unroll
                for (int qq = (i == 2 ? 0 : 3); qq <= i; qq++) {
                    float c0[4] = {0.f, 0.f, 0.f, 0.f}, c1[4] = {0.f, 0.f, 0.f, 0.f}, c2[4] = {0.f, 0.f, 0.f, 0.f};
                    mma16816(c0, a[qq][0], bf[0], bf[1]);
                    mma16816(c1, a[qq][1], bf[2], bf[3]);
                    mma16816(c2, a[qq][2], bf[4], bf[5]);
                    mma16816(c0, a[qq][3], bf[6], bf[7]);
                    mma16816(c1, a[qq][4], bf[8], bf[9]);
                    if (t4 == qq) {
                        v0 = (c0[0] + c1[0]) + c2[0];
                        v1 = (c0[2] + c1[2]) + c2[2];
                    }
                }
                old[i - 2] = make_float4(0.f, 0.f, 0.f, 0.f);
                if (live && (i == 2 ? t4 < 3 : t4 == 3))
                    asm volatile("atom.relaxed.gpu.global.add.v4.f32 {%0,%1,%2,%3}, [%4], {%5,%6,%7,%8};"
                                 : "=f"(old[i - 2].x), "=f"(old[i - 2].y), "=f"(old[i - 2].z), "=f"(old[i - 2].w)
                                 : "l"(acc), "f"(v0), "f"(v1), "f"(1.0f), "f"(0.0f) : "memory");
            }
            if (live && tid == 160) TRACE_PT(10);
            const float cnt = (old[1].z + old[0].z) + (old[1].w + old[0].w);
            const uint32_t res = pack_bf((old[1].x + old[0].x) + (xres0 + v0), (old[1].y + old[0].y) + (xres1 + v1));
            asm volatile(
                "{\n.reg .pred p;\n.reg .b16 lo, hi;\n"
                "setp.eq.f32 p, %0, 0f42FE0000;\n"
                "mov.b32 {lo, hi}, %1;\n"
                "@p st.global.b16 [%2], lo;\n"
                "@p st.global.b16 [%2+16], hi;\n"
                "@p st.global.v4.f32 [%3], {0f00000000, 0f00000000, 0f00000000, 0f00000000};\n}"
                ::"f"(cnt), "r"(res), "l"(out + ocol), "l"(acc) : "memory");
            if (live && tid == 160 + 3) TRACE_PT(11);
        }
    }
    return;
    }

    {
        const int kvrow = g8 * SK + (SK - WIN) + s8 * 64;
        if (tid == 0) {
            TRACE_PT(13);
#pragma unroll
            for (int j = 0; j < NFIRST; j++) {
                const uint32_t bar = full0 + 8 * j;
                mbar_init(bar, 1);
                asm volatile("fence.mbarrier_init.release.cluster;" ::: "memory");
                mbar_expect_tx(bar, j < T_K ? WQ_BYTES : KV_BYTES);
                if (j < T_K) tma3d(smem_base + SM_WQ + j * WQ_BYTES, &maps.wq, 0, r4 * 144 + j * 48, q4 * 2, bar);
                else tma3d(smem_base + (j - T_K) * KV_BYTES, &maps.k, 0, kvrow + (j - T_K) * 512, 0, bar);
                if (j == 0) TRACE_PT(0);
            }
        }
        __syncthreads();
        if (tid == 0) {
            TRACE_PT(15);
#pragma unroll 1
            for (int i = NFIRST; i < NTILE; i++) {
                int c0 = 0, c1, c2 = 0, c1b, bytes, bytes1, mi, dst;
                if (i < T_GU) {
                    mi = (i < T_V) ? 1 : 2; c1 = kvrow + ((i - T_K) & 7) * 512; c1b = 0;
                    bytes = KV_BYTES; bytes1 = 0; dst = (i - T_K) * KV_BYTES;
                    if (dst >= KV_WRAP) dst -= KV_WRAP;
                } else if (i < T_W) {
                    mi = 3; c0 = (b * 36) & ~7; c1 = c1b = (i - T_GU) * 144;
                    bytes = 2 * G_BYTES; bytes1 = G_BYTES; dst = SM_GU + (i - T_GU) * (2 * G_BYTES);
                } else {
                    mi = 5; c1 = b * 32; c1b = b * 36; c2 = (i - T_W) * 2;
                    bytes = WO_BYTES + WD_BYTES; bytes1 = WO_BYTES; dst = SM_W + (i - T_W) * (WO_BYTES + WD_BYTES);
                }
                const uint32_t bar = full0 + 8 * i;
                if (i == T_V + 3 || i == T_V + 5 || i == T_GU || i == T_W - 1)
                    mbar_wait0(dep0 + 8 * (i == T_V + 3 ? REL_WQ : i == T_V + 5 ? REL_K : i == T_GU ? DEP_P : REL_V));
                mbar_expect_tx(bar, bytes);
                const int back = (i < WIN_AT1) ? INFLIGHT : (i < WIN_AT2) ? INFLIGHT2 : INFLIGHT3;
                mbar_wait0(bar - 8 * back);
                tma3d(smem_base + dst, &maps.wq + mi, c0, c1, c2, bar);
                if (bytes1) tma3d(smem_base + dst + bytes1, &maps.wq + mi + 1, c0, c1b, c2, bar);
                TRACE_PT(32 + i);
            }
        }
    }

}

typedef CUresult (*EncodeFn)(CUtensorMap*, CUtensorMapDataType, cuuint32_t, void*, const cuuint64_t*,
                             const cuuint64_t*, const cuuint32_t*, const cuuint32_t*, CUtensorMapInterleave,
                             CUtensorMapSwizzle, CUtensorMapL2promotion, CUtensorMapFloatOOBfill);

void make_map(EncodeFn enc, CUtensorMap* m, const void* base, uint64_t inner, uint64_t rows, uint64_t ngroups,
              uint64_t row_bytes, uint32_t box_inner, uint32_t box_rows, uint32_t box_groups, CUtensorMapSwizzle sw,
              CUtensorMapL2promotion prom) {
    cuuint64_t dims[3] = {inner, rows, ngroups};
    cuuint64_t strides[2] = {row_bytes, inner * 2};
    cuuint32_t box[3] = {box_inner, box_rows, box_groups};
    cuuint32_t es[3] = {1, 1, 1};
    enc(m, CU_TENSOR_MAP_DATA_TYPE_BFLOAT16, 3, const_cast<void*>(base), dims, strides, box, es,
        CU_TENSOR_MAP_INTERLEAVE_NONE, sw, prom, CU_TENSOR_MAP_FLOAT_OOB_FILL_NONE);
}

}

extern "C" void kernel_launch(void* const* d_in, const int* in_sizes, int n_in, void* d_out, int out_size) {
    (void)in_sizes; (void)n_in; (void)out_size;
    static EncodeFn enc = nullptr;
    static void* scratch = nullptr;
    if (!enc) {
        cudaGetSymbolAddress(&scratch, g_scratch);
        cudaDriverEntryPointQueryResult qr;
        void* fn = nullptr;
        cudaGetDriverEntryPoint("cuTensorMapEncodeTiled", &fn, cudaEnableDefault, &qr);
        enc = (EncodeFn)fn;
        cudaFuncSetAttribute(fused_decode_kernel, cudaFuncAttributeMaxDynamicSharedMemorySize, SMEM_BYTES);
    }
    const CUtensorMapL2promotion P128 = CU_TENSOR_MAP_L2_PROMOTION_L2_128B, P256 = CU_TENSOR_MAP_L2_PROMOTION_L2_256B;
    Maps maps;
    make_map(enc, &maps.wq, d_in[3], 64, 576, 64, 8192, 64, 48, 2, CU_TENSOR_MAP_SWIZZLE_128B, P256);
    make_map(enc, &maps.k, d_in[1], 64, 16ull * SK, 2, 256, 64, 64, 2, CU_TENSOR_MAP_SWIZZLE_128B, P256);
    make_map(enc, &maps.v, d_in[2], 64, 16ull * SK, 2, 256, 64, 64, 2, CU_TENSOR_MAP_SWIZZLE_128B, P256);
    make_map(enc, &maps.wg, d_in[6], 4608, 576, 1, 9216, 40, 144, 1, CU_TENSOR_MAP_SWIZZLE_NONE, P128);
    make_map(enc, &maps.wu, d_in[7], 4608, 576, 1, 9216, 40, 144, 1, CU_TENSOR_MAP_SWIZZLE_NONE, P128);
    make_map(enc, &maps.wo, d_in[4], 72, 4096, 8, 1152, 72, 32, 2, CU_TENSOR_MAP_SWIZZLE_NONE, P256);
    make_map(enc, &maps.wd, d_in[8], 72, 4608, 8, 1152, 72, 36, 2, CU_TENSOR_MAP_SWIZZLE_NONE, P256);
    fused_decode_kernel<<<NCTA, NTHREADS, SMEM_BYTES, cudaStreamPerThread>>>(
        (const __nv_bfloat16*)d_in[0], (__nv_bfloat16*)d_out, (Scratch*)scratch, maps);
}
```

```cpp
#include <cuda_runtime.h>
#include <cuda_bf16.h>
#include <cuda.h>
#include <stdint.h>
#include <stddef.h>

namespace {

constexpr int D_MODEL = 576;
constexpr int SK = 65536;
constexpr int WIN = 4096;
constexpr int NCTA = 128;

#define QTIMER 2
#define XTIMER 0
#define ACC_STRIDE 9
#define ACC_UNIT 8
#define ACC_IDX(p) (((p) / ACC_UNIT) * (ACC_UNIT * ACC_STRIDE) + ((p) % ACC_UNIT))
#define OTIMER 1
#define NFIRST_ 4
constexpr int NFIRST = NFIRST_;
#define WIN_LO 0x3333333333344444ull
#define WIN_HI 0x400333333333ull
#define PACE 79
#define SCHED0 300
#define CATCHUP 3
constexpr int T_K = 4;
constexpr int T_V = 12;
constexpr int T_GU = 20;
constexpr int T_WO = 24;
constexpr int T_WD = 27;
constexpr int NTILE = 36;

constexpr int KV_BYTES = 16384;
constexpr int KV_WRAP = 13 * KV_BYTES;
constexpr int WQ_BYTES = 144 * 64;
constexpr int G_BYTES = 144 * 80;
constexpr int WO_BYTES = 32 * 384, WD_BYTES = 36 * 128;
constexpr int SM_WQ = 11 * KV_BYTES;
constexpr int SM_GU = 3 * KV_BYTES;
constexpr int SM_WO = SM_GU + 8 * G_BYTES;
constexpr int SM_WD = SM_WO + 3 * WO_BYTES;
constexpr int SM_END = SM_WD + 9 * WD_BYTES;
static_assert(SM_WO % 1024 == 0 && SM_WD % 1024 == 0, "swizzle phase");

constexpr int NMMA_WARPS = 9;
constexpr int NGATHER_WARPS = 4;
constexpr int NTHREADS = (NMMA_WARPS + NGATHER_WARPS + 1) * 32;
constexpr int P_PITCH = 520;

struct Maps {
    CUtensorMap wq, k, v, wg, wu, wo, wd;
};

constexpr int DEP_X = 0, DEP_O = 1, DEP_Q = 2, DEP_H = 3, DEP_P = 4, REL_K = 5, REL_V = 6, DEP_QP = 7, DEP_GU = 8;
struct SmemMisc {
    unsigned long long full[NTILE];
    unsigned long long dep[22];
    __nv_bfloat16 xn[576];
    __nv_bfloat16 o[32];
    __nv_bfloat16 h[48];
    __nv_bfloat16 q[256];
    __nv_bfloat16 s[2 * 512];
    __nv_bfloat16 p[4 * P_PITCH];
    float red[9 * 40 * 2];
    float wmax[16];
    float wsum[16];
};
constexpr int SMEM_BYTES = SM_END + (int)sizeof(SmemMisc) + 1024;
static_assert(SMEM_BYTES <= 232448, "smem");

constexpr int OFF_Q = 0;
constexpr int OFF_O = NCTA * 8;
constexpr int OFF_ML = OFF_O + 32 * 8 * 64;
constexpr int NREC = OFF_ML + 256;
struct Scratch {
    uint4 rec[NREC];
    float4 acc[288 * ACC_STRIDE];
    unsigned epoch[NCTA];
};
__device__ __align__(128) Scratch g_scratch;

#define TRACE_PT(i) do { } while (0)
#define CLK_PT(i) do { } while (0)

constexpr unsigned SPIN_LIMIT = 1u << 24;

__device__ __forceinline__ uint32_t smem_u32(const void* p) { return (uint32_t)__cvta_generic_to_shared(p); }
__device__ __forceinline__ void mbar_init(uint32_t bar, int cnt) {
    asm volatile("mbarrier.init.shared::cta.b64 [%0], %1;" ::"r"(bar), "r"(cnt) : "memory");
}
__device__ __forceinline__ void mbar_expect_tx(uint32_t bar, uint32_t bytes) {
    asm volatile("mbarrier.arrive.expect_tx.shared::cta.b64 _, [%0], %1;" ::"r"(bar), "r"(bytes) : "memory");
}
__device__ __forceinline__ void mbar_arrive(uint32_t bar) {
    asm volatile("mbarrier.arrive.shared::cta.b64 _, [%0];" ::"r"(bar) : "memory");
}
__device__ __forceinline__ bool mbar_test0(uint32_t bar) {
    uint32_t ok;
    asm volatile(
        "{\n.reg .pred p;\n"
        "mbarrier.test_wait.parity.shared::cta.b64 p, [%1], 0;\n"
        "selp.u32 %0, 1, 0, p;\n}"
        : "=r"(ok) : "r"(bar) : "memory");
    return ok;
}
__device__ __forceinline__ void mbar_wait0(uint32_t bar) {
    unsigned it = 0;
    while (true) {
        uint32_t ok;
        asm volatile(
            "{\n.reg .pred p;\n"
            "mbarrier.try_wait.parity.shared::cta.b64 p, [%1], 0;\n"
            "selp.u32 %0, 1, 0, p;\n}"
            : "=r"(ok) : "r"(bar) : "memory");
        if (ok) break;
        if (++it > SPIN_LIMIT) __trap();
    }
}
__device__ __forceinline__ void tma3d(uint32_t dst, const CUtensorMap* m, int c0, int c1, int c2, uint32_t bar) {
    asm volatile(
        "cp.async.bulk.tensor.3d.shared::cluster.global.mbarrier::complete_tx::bytes [%0], [%1, {%3, %4, %5}], [%2];"
        ::"r"(dst), "l"(m), "r"(bar), "r"(c0), "r"(c1), "r"(c2) : "memory");
}
__device__ __forceinline__ void ldsm4(uint32_t (&r)[4], uint32_t addr) {
    asm volatile("ldmatrix.sync.aligned.m8n8.x4.shared.b16 {%0,%1,%2,%3}, [%4];"
                 : "=r"(r[0]), "=r"(r[1]), "=r"(r[2]), "=r"(r[3]) : "r"(addr) : "memory");
}
__device__ __forceinline__ void ldsm4t(uint32_t (&r)[4], uint32_t addr) {
    asm volatile("ldmatrix.sync.aligned.m8n8.x4.trans.shared.b16 {%0,%1,%2,%3}, [%4];"
                 : "=r"(r[0]), "=r"(r[1]), "=r"(r[2]), "=r"(r[3]) : "r"(addr) : "memory");
}
__device__ __forceinline__ void mma16816(float (&c)[4], const uint32_t (&a)[4], uint32_t b0, uint32_t b1) {
    asm volatile(
        "mma.sync.aligned.m16n8k16.row.col.f32.bf16.bf16.f32 {%0,%1,%2,%3}, {%4,%5,%6,%7}, {%8,%9}, {%0,%1,%2,%3};"
        : "+f"(c[0]), "+f"(c[1]), "+f"(c[2]), "+f"(c[3])
        : "r"(a[0]), "r"(a[1]), "r"(a[2]), "r"(a[3]), "r"(b0), "r"(b1));
}
__device__ __forceinline__ void mma1688(float (&c)[4], uint32_t a0, uint32_t a1, uint32_t b0) {
    asm volatile(
        "mma.sync.aligned.m16n8k8.row.col.f32.bf16.bf16.f32 {%0,%1,%2,%3}, {%4,%5}, {%6}, {%0,%1,%2,%3};"
        : "+f"(c[0]), "+f"(c[1]), "+f"(c[2]), "+f"(c[3])
        : "r"(a0), "r"(a1), "r"(b0));
}
__device__ __forceinline__ void bar_sync(int id, int n) { asm volatile("bar.sync %0, %1;" ::"r"(id), "r"(n) : "memory"); }

__device__ __forceinline__ unsigned long long pack64(uint32_t lo, uint32_t hi) {
    return ((unsigned long long)hi << 32) | lo;
}
__device__ __forceinline__ void st_rec2(uint4* p, float v0, float v1, uint32_t tag) {
    asm volatile("st.relaxed.gpu.global.v2.b64 [%0], {%1, %2};" ::"l"(p), "l"(pack64(__float_as_uint(v0), tag)),
                 "l"(pack64(__float_as_uint(v1), tag)) : "memory");
}
__device__ __forceinline__ uint4 ld_rec2(const uint4* p) {
    unsigned long long a, b;
    asm volatile("ld.relaxed.gpu.global.v2.b64 {%0, %1}, [%2];" : "=l"(a), "=l"(b) : "l"(p) : "memory");
    return make_uint4((uint32_t)a, (uint32_t)(a >> 32), (uint32_t)b, (uint32_t)(b >> 32));
}
__device__ __forceinline__ float4 atom_add_count(float4* p, float v0, float v1, bool pred) {
    float4 o = make_float4(0.f, 0.f, 0.f, 0.f);
    asm volatile(
        "{\n.reg .pred p;\nsetp.ne.u32 p, %7, 0;\n"
        "@p atom.relaxed.gpu.global.add.v4.f32 {%0,%1,%2,%3}, [%4], {%5,%6,0f3F800000,0f00000000};\n}"
        : "+f"(o.x), "+f"(o.y), "+f"(o.z), "+f"(o.w)
        : "l"(p), "f"(v0), "f"(v1), "r"((uint32_t)pred) : "memory");
    return o;
}
__device__ __forceinline__ float bf16r(float x) { return __bfloat162float(__float2bfloat16_rn(x)); }
__device__ __forceinline__ float bf_lo(uint32_t u) { return __uint_as_float(u << 16); }
__device__ __forceinline__ float bf_hi(uint32_t u) { return __uint_as_float(u & 0xffff0000u); }
__device__ __forceinline__ uint32_t pack_bf(float lo, float hi) {
    __nv_bfloat162 v = __floats2bfloat162_rn(lo, hi);
    return *reinterpret_cast<uint32_t*>(&v);
}
__device__ __forceinline__ uint32_t lds32(uint32_t a) {
    uint32_t v;
    asm volatile("ld.shared.b32 %0, [%1];" : "=r"(v) : "r"(a) : "memory");
    return v;
}
__device__ __forceinline__ float2 lds64f(uint32_t a) {
    float2 v;
    asm volatile("ld.shared.v2.f32 {%0, %1}, [%2];" : "=f"(v.x), "=f"(v.y) : "r"(a) : "memory");
    return v;
}
__device__ __forceinline__ void sts32(uint32_t a, uint32_t v) { asm volatile("st.shared.b32 [%0], %1;" ::"r"(a), "r"(v) : "memory"); }
__device__ __forceinline__ void sts64(uint32_t a, uint32_t x, uint32_t y) {
    asm volatile("st.shared.v2.b32 [%0], {%1, %2};" ::"r"(a), "r"(x), "r"(y) : "memory");
}
__device__ __forceinline__ void sts64f(uint32_t a, float x, float y) {
    asm volatile("st.shared.v2.f32 [%0], {%1, %2};" ::"r"(a), "f"(x), "f"(y) : "memory");
}
__device__ __forceinline__ void sts_bf16(uint32_t a, float v) {
    asm volatile("{\n.reg .b16 h;\ncvt.rn.bf16.f32 h, %1;\nst.shared.b16 [%0], h;\n}" ::"r"(a), "f"(v) : "memory");
}
__device__ __forceinline__ float ex2(float x) {
    float y;
    asm("ex2.approx.ftz.f32 %0, %1;" : "=f"(y) : "f"(x));
    return y;
}
__device__ __forceinline__ float shx(float v, int m) { return __shfl_xor_sync(0xffffffffu, v, m); }
constexpr float L2E = 1.4426950408889634f;
#define MISC(f) (misc + (uint32_t)offsetof(SmemMisc, f))

__global__ void __launch_bounds__(NTHREADS, 1)
fused_decode_kernel(const __nv_bfloat16* __restrict__ x, __nv_bfloat16* __restrict__ out, Scratch* __restrict__ scr,
                    const __grid_constant__ Maps maps) {
    uint4* const g_rec = scr->rec;
    float4* const g_acc = scr->acc;
    unsigned* const g_epoch = scr->epoch;
    extern __shared__ unsigned char smem_raw[];
    const uint32_t smem_base = (smem_u32(smem_raw) + 1023u) & ~1023u;
    const uint32_t misc = smem_base + SM_END;
    const uint32_t full0 = MISC(full);
    const uint32_t dep0 = MISC(dep);

    const int tid = threadIdx.x;
    const int b = blockIdx.x;
    const int q4 = b >> 2, r4 = b & 3;
    const int g8 = b >> 3, s8 = b & 7;

    if (tid >= 32) {
    const int warp = __shfl_sync(0xffffffffu, tid >> 5, 0);
    const int lane = tid & 31;
    uint32_t tag, xs[9];
    if (warp == 1) {
#pragma unroll
        for (int j = 0; j < 9; j++)
            asm volatile("ld.global.nc.u32 %0, [%1];" : "=r"(xs[j]) : "l"(reinterpret_cast<const uint32_t*>(x) + lane + 32 * j));
    }
    asm volatile("ld.relaxed.gpu.global.u32 %0, [%1];" : "=r"(tag) : "l"(&g_epoch[b]) : "memory");
    if (lane == 0) {
#pragma unroll
        for (int j = 0; j < 4; j++) {
            const int i = NFIRST - 4 + warp * 4 + j;
            mbar_init(full0 + 8 * i, (i < NTILE + DEP_H) ? 1 : (i == NTILE + DEP_H) ? 2 : (i < NTILE + DEP_QP) ? 8 : 9);
        }
        asm volatile("fence.mbarrier_init.release.cluster;" ::: "memory");
    }
    __syncthreads();

    if (warp <= NGATHER_WARPS) {
        if (warp == 1) {
            float s = 0.f;
#pragma unroll
            for (int j = 0; j < 9; j++) s += bf_lo(xs[j]) + bf_hi(xs[j]);
#pragma unroll
            for (int off = 16; off >= 1; off >>= 1) s += shx(s, off);
            const float mean = s * (1.0f / D_MODEL);
            float v = 0.f;
#pragma unroll
            for (int j = 0; j < 9; j++) {
                float d0 = bf_lo(xs[j]) - mean, d1 = bf_hi(xs[j]) - mean;
                v += d0 * d0 + d1 * d1;
            }
#pragma unroll
            for (int off = 16; off >= 1; off >>= 1) v += shx(v, off);
            const float mb = bf16r(mean);
            float den;
            asm("sqrt.approx.f32 %0, %1;" : "=f"(den) : "f"(bf16r(bf16r(v * (1.0f / D_MODEL)) + 1e-5f)));
            const float inv = __fdividef(1.0f, bf16r(den));
#pragma unroll
            for (int j = 0; j < 9; j++)
                sts32(MISC(xn) + (lane + 32 * j) * 4, pack_bf(bf16r(bf_lo(xs[j]) - mb) * inv, bf16r(bf_hi(xs[j]) - mb) * inv));
            __syncwarp();
            if (lane == 0) mbar_arrive(dep0 + 8 * DEP_X);
            if (lane == 0) TRACE_PT(1);
        }
        const int gw = warp - 1;

        float w0 = 0.f, w1 = 0.f, w2 = 0.f, w3 = 0.f;
#pragma unroll 1
        for (uint32_t prog = (0xBA32'0C41'0C45'009Dull >> (16 * gw)) & 0xffff; prog; prog >>= 4) {
            const bool live = prog & 8;
            const int step = prog & 7;
            if (live) asm volatile("or.b32 %0, %0, 0x80000000;" : "+r"(tag));
            if (step >= 4) {
                if (live && gw == 2 && b < 9) {
                    const uint32_t xx = reinterpret_cast<const uint32_t*>(x)[b * 32 + lane];
                    mbar_wait0(full0 + 8 * (T_V + XTIMER));
                    asm volatile("red.relaxed.gpu.global.add.v4.f32 [%0], {%1,%2,0f3F800000,0f00000000};"
                                 ::"l"(g_acc + ACC_IDX(b * 32 + lane)), "f"(bf_lo(xx)), "f"(bf_hi(xx)) : "memory");
                }
                if (live) mbar_wait0(dep0 + 8 * (step == 4 ? DEP_GU : DEP_QP));
                const int j = (gw & 2) * 16 + lane;
                const uint32_t ra = MISC(red) + (min(j, 35) + (step == 4 ? (b & 1) << 2 : 0)) * 8;
                float g = 0.f, u = 0.f;
#pragma unroll
                for (int w = 0; w < 9; w++) {
                    const float2 t = lds64f(ra + w * 320);
                    g += t.x;
                    u += t.y;
                }
                if (step == 4) {
                    g = bf16r(g);
                    const float k = -2.0f * 0.7978845608028654f * L2E;
                    const float hv = bf16r(__fdividef(g, 1.0f + ex2(k * (g + 0.044715f * g * g * g)))) * bf16r(u);
                    if (live && j < 40) sts_bf16(MISC(h) + j * 2, j < 36 ? hv : 0.f);
                    __syncwarp();
                    if (live && lane == 0) mbar_arrive(dep0 + 8 * DEP_H);
                    if (live && tid == 64) TRACE_PT(5);
                } else {
                    const float other = shx((lane & 1) ? g : u, 1);
                    const uint32_t word = (lane & 1) ? pack_bf(other, u) : pack_bf(g, other);
                    const int wi = (lane & 8) + ((lane & 7) >> 1) + (lane & 1) * 4;
                    if (live && lane < 16)
                        asm volatile("st.relaxed.gpu.global.b64 [%0], %1;" ::"l"(reinterpret_cast<uint2*>(g_rec + OFF_Q + b * 8) + wi),
                                     "l"(pack64(word, tag)) : "memory");
                    if (live && lane == 0) TRACE_PT(2);
                }
                continue;
            }
            uint4 r0 = make_uint4(0, 0, 0, 0), r1 = r0, r2 = r0, r3 = r0;
            {
                int idx, stride;
                uint32_t wbar;
                if (step == 1) { idx = OFF_Q + g8 * 64 + (lane & 15); stride = 16; wbar = full0 + 8 * (T_K + QTIMER); }
                else if (step == 2) { idx = OFF_ML + (g8 * 8 + (lane & 1) * 4) * 2 + (q4 & 1); stride = 2; wbar = full0 + 8 * (T_V + 6); }
                else { idx = OFF_O + (q4 * 8 + (lane & 1) * 4) * 64 + r4 * 16 + (lane >> 1); stride = 64; wbar = full0 + 8 * (T_GU + OTIMER); }
                const uint32_t want = live ? tag : 0u;
                if (live) mbar_wait0(wbar);
                if (live && lane == 0) TRACE_PT(15 + step);
                const uint4* src = g_rec + idx;
                unsigned it = 0;
                while (true) {
                    if (r0.y != want || r0.w != want) r0 = ld_rec2(src);
                    if (r1.y != want || r1.w != want) r1 = ld_rec2(src + stride);
                    if (r2.y != want || r2.w != want) r2 = ld_rec2(src + 2 * stride);
                    if (r3.y != want || r3.w != want) r3 = ld_rec2(src + 3 * stride);
                    const uint32_t bad = ((r0.y ^ want) | (r0.w ^ want) | (r1.y ^ want)) | ((r1.w ^ want) | (r2.y ^ want) | (r2.w ^ want)) |
                                         ((r3.y ^ want) | (r3.w ^ want));
                    if (bad == 0) break;
                    if (++it > SPIN_LIMIT) __trap();
                }
                __syncwarp();
            }
            const float a0 = __uint_as_float(r0.x), a1 = __uint_as_float(r1.x), a2 = __uint_as_float(r2.x), a3 = __uint_as_float(r3.x);
            const float b0 = __uint_as_float(r0.z), b1 = __uint_as_float(r1.z), b2 = __uint_as_float(r2.z), b3 = __uint_as_float(r3.z);
            if (step == 2) {
                float mx = fmaxf(fmaxf(a0, a1), fmaxf(a2, a3));
                mx = fmaxf(mx, shx(mx, 1));
                w0 = ex2((a0 - mx) * L2E); w1 = ex2((a1 - mx) * L2E); w2 = ex2((a2 - mx) * L2E); w3 = ex2((a3 - mx) * L2E);
                float L = w0 * b0 + w1 * b1 + w2 * b2 + w3 * b3;
                L += shx(L, 1);
                const float inv = __fdividef(1.0f, L);
                w0 *= inv; w1 *= inv; w2 *= inv; w3 *= inv;
            } else if (step == 3) {
                const float u = w0 * a0 + w1 * a1 + w2 * a2 + w3 * a3;
                const float v = w0 * b0 + w1 * b1 + w2 * b2 + w3 * b3;
                const float tot = ((lane & 1) ? v : u) + shx((lane & 1) ? u : v, 1);
                if (live) sts_bf16(MISC(o) + ((lane & 16) + ((lane >> 1) & 7) + (lane & 1) * 8) * 2, tot);
                __syncwarp();
                if (live && lane == 0) mbar_arrive(dep0 + 8 * DEP_O);
                if (live && lane == 0) TRACE_PT(8);
            } else {
                const uint32_t qa = MISC(q) + (lane & 15) * 8;
                if (live) {
                    sts64(qa, r0.x, r0.z);
                    sts64(qa + 128, r1.x, r1.z);
                    sts64(qa + 256, r2.x, r2.z);
                    sts64(qa + 384, r3.x, r3.z);
                }
                __syncwarp();
                if (live && lane == 0) mbar_arrive(dep0 + 8 * DEP_Q);
                if (live && lane == 0) TRACE_PT(4);
            }
        }
        return;
    }

    const int mw = warp - 1 - NGATHER_WARPS;
    const int gq = lane >> 2, t4 = lane & 3;
    const int lrow = (lane & 7) + ((lane >> 4) << 3);
    const int lchk = (lane >> 3) & 1;
    const int opair = mw * 32 + t4 * 8 + (gq >> 1) + (gq & 1) * 4;
    uint4* const rec_o = g_rec + OFF_O + ((g8 * 2 + (t4 & 1)) * 8 + s8) * 64 + mw * 8 + gq;

#pragma unroll 1
    for (int it0 = -1; it0 < 6; it0++) {
        const bool live = it0 >= 0;
        if (live) asm volatile("or.b32 %0, %0, 0x80000000;" : "+r"(tag));
        int sec = live ? it0 : (mw >= 7 ? 0 : mw);
        if (live && mw == 8 && sec >= 1 && sec < 4) {
            if (sec != 3) continue;
            sec = 6;
        }
        if (sec == 0 || sec == 4) {
            const bool gu = sec;
            float acc[5][4];
#pragma unroll
            for (int c = 0; c < 5; c++) acc[c][0] = acc[c][1] = acc[c][2] = acc[c][3] = 0.f;
            const int sw = (lane >> 1) & 3;
            uint32_t base = smem_base + (gu ? SM_GU + lchk * G_BYTES + (mw * 16 + lrow) * 80
                                            : SM_WQ + (mw * 16 + lrow) * 64 + ((lchk ^ sw) << 4));
            const int cstride = gu ? 16 : (sw & 2) ? -32 : 32;
            uint32_t baddr = MISC(xn) + mw * 32 + t4 * 4;
            uint32_t bar = full0 + (gu ? 8 * T_GU : 0);
            if (live) mbar_wait0(dep0 + 8 * DEP_X);
#pragma unroll 1
            for (int i = live ? 0 : 3; i < 4; i++) {
                const uint32_t b0 = lds32(baddr), b1 = lds32(baddr + 16);
                baddr += 288;
                if (live) mbar_wait0(bar);
                bar += 8;
                uint32_t a[5][4];
                ldsm4t(a[0], base);
                ldsm4t(a[1], base + cstride);
                if (gu) {
                    ldsm4t(a[2], base + 32);
                    ldsm4t(a[3], base + 48);
                    ldsm4t(a[4], base + 64);
                }
                mma16816(acc[0], a[0], b0, b1);
                mma16816(acc[1], a[1], b0, b1);
                if (gu) {
                    mma16816(acc[2], a[2], b0, b1);
                    mma16816(acc[3], a[3], b0, b1);
                    mma16816(acc[4], a[4], b0, b1);
                }
                base += gu ? 2 * G_BYTES : WQ_BYTES;
            }
            const uint32_t red = MISC(red) + (mw * 40 + gq) * 8;
            sts64f(red + t4 * 64, t4 == 0 ? acc[0][0] : t4 == 1 ? acc[1][0] : t4 == 2 ? acc[2][0] : acc[3][0],
                   t4 == 0 ? acc[0][2] : t4 == 1 ? acc[1][2] : t4 == 2 ? acc[2][2] : acc[3][2]);
            if (t4 == 0) sts64f(red + 256, acc[4][0], acc[4][2]);
            __syncwarp();
            if (live && lane == 0) mbar_arrive(dep0 + 8 * (gu ? DEP_GU : DEP_QP));
        } else if (sec == 1) {
            if (live) mbar_wait0(dep0 + 8 * DEP_Q);
            uint32_t qb[16];
#pragma unroll
            for (int j = 0; j < 16; j++) qb[j] = lds32(MISC(q) + (gq & 1) * 256 + t4 * 4 + j * 16);
            const int krow = (mw & 3) * 16 + (lane & 15);
            float m = -INFINITY;
#pragma unroll 1
            for (int i = live ? 0 : 3; i < 4; i++) {
                const int kt = (mw >> 2) + 2 * i;
                const uint32_t base = smem_base + kt * KV_BYTES + krow * 128;
                if (live) mbar_wait0(full0 + 8 * (T_K + kt));
                float c0[4] = {0.f, 0.f, 0.f, 0.f}, c1[4] = {0.f, 0.f, 0.f, 0.f};
#pragma unroll
                for (int ks = 0; ks < 4; ks++) {
                    uint32_t a0[4], a1[4];
                    const uint32_t sw = ((ks * 2 + (lane >> 4)) ^ (lane & 7)) << 4;
                    ldsm4(a0, base + sw);
                    ldsm4(a1, base + 8192 + sw);
                    mma16816(c0, a0, qb[2 * ks], qb[2 * ks + 1]);
                    mma16816(c1, a1, qb[8 + 2 * ks], qb[8 + 2 * ks + 1]);
                }
                __syncwarp();
                if (i == 1 && lane == 0) mbar_arrive(dep0 + 8 * REL_K);
                const float lo = (t4 & 1) ? c0[1] + c1[1] : c0[0] + c1[0];
                const float hi = (t4 & 1) ? c0[3] + c1[3] : c0[2] + c1[2];
                const float sc = bf16r(bf16r((t4 & 2) ? hi : lo) * 0.08838834764831845f);
                m = fmaxf(m, sc);
                sts_bf16(MISC(s) + ((t4 & 1) * 512 + kt * 64 + (mw & 3) * 16 + gq + (t4 & 2) * 4) * 2, sc);
            }
#pragma unroll
            for (int off = 2; off <= 16; off <<= 1) m = fmaxf(m, shx(m, off));
            if (lane < 2) sts32(MISC(wmax) + mw * 8 + lane * 4, __float_as_uint(m));
        } else if (sec == 2) {
            if (live) bar_sync(1, 256);
            float m0 = -INFINITY, m1 = -INFINITY;
#pragma unroll
            for (int j = 0; j < 8; j++) {
                m0 = fmaxf(m0, __uint_as_float(lds32(MISC(wmax) + j * 8)));
                m1 = fmaxf(m1, __uint_as_float(lds32(MISC(wmax) + j * 8 + 4)));
            }
            const int kp = mw * 32 + lane;
            const uint32_t s0 = lds32(MISC(s) + kp * 4);
            const uint32_t s1 = lds32(MISC(s) + 1024 + kp * 4);
            const float p00 = ex2((bf_lo(s0) - m0) * L2E), p01 = ex2((bf_hi(s0) - m0) * L2E);
            const float p10 = ex2((bf_lo(s1) - m1) * L2E), p11 = ex2((bf_hi(s1) - m1) * L2E);
            const uint32_t h0 = pack_bf(p00, p01), h1 = pack_bf(p10, p11);
            const uint32_t pa = MISC(p) + kp * 4;
            sts32(pa, h0);
            sts32(pa + P_PITCH * 2, pack_bf(p00 - bf_lo(h0), p01 - bf_hi(h0)));
            sts32(pa + P_PITCH * 4, h1);
            sts32(pa + P_PITCH * 6, pack_bf(p10 - bf_lo(h1), p11 - bf_hi(h1)));
            const float l0 = p00 + p01, l1 = p10 + p11;
            float l = ((lane & 1) ? l1 : l0) + shx((lane & 1) ? l0 : l1, 1);
#pragma unroll
            for (int off = 2; off <= 16; off <<= 1) l += shx(l, off);
            if (lane < 2) sts32(MISC(wsum) + mw * 8 + lane * 4, __float_as_uint(l));
            __syncwarp();
            if (live && lane == 0) mbar_arrive(dep0 + 8 * DEP_P);
            if (live && tid == 160) TRACE_PT(6);
        } else if (sec == 3) {
            const uint32_t a_off = smem_base + lrow * 128 + ((((mw & 3) * 2 + lchk) ^ (lane & 7)) << 4) + (mw & 4) * 2048;
            int taddr = 8 * KV_BYTES;
            uint32_t baddr = t4 * 4 + MISC(p) + (gq & 3) * (P_PITCH * 2);
            if (live) mbar_wait0(dep0 + 8 * DEP_P);
            float c0[4] = {0.f, 0.f, 0.f, 0.f}, c1[4] = {0.f, 0.f, 0.f, 0.f};
#pragma unroll 1
            for (int i = live ? 0 : 7; i < 8; i++) {
                const uint32_t base = a_off + taddr;
                taddr += KV_BYTES;
                if (taddr >= KV_WRAP) taddr -= KV_WRAP;
                uint32_t bf[8];
#pragma unroll
                for (int j = 0; j < 8; j++) bf[j] = lds32(baddr + j * 16);
                baddr += 128;
                if (live) mbar_wait0(full0 + 8 * (T_V + i));
                uint32_t a0[4], a1[4], a2[4], a3[4];
                ldsm4t(a0, base);
                ldsm4t(a1, base + 2048);
                ldsm4t(a2, base + 4096);
                ldsm4t(a3, base + 6144);
                mma16816(c0, a0, bf[0], bf[1]);
                mma16816(c1, a1, bf[2], bf[3]);
                mma16816(c0, a2, bf[4], bf[5]);
                mma16816(c1, a3, bf[6], bf[7]);
                __syncwarp();
                if (i == 4) {
                    if (lane == 0) mbar_arrive(dep0 + 8 * REL_V);
                    if (t4 < 2) st_rec2(rec_o, 0.f, 0.f, 0u);
                }
            }
            if (live && t4 < 2) st_rec2(rec_o, (c0[0] + c1[0]) + (c0[1] + c1[1]), (c0[2] + c1[2]) + (c0[3] + c1[3]), tag);
            if (live && tid == 160) TRACE_PT(7);
        } else if (sec == 6) {
            if (live) mbar_wait0(dep0 + 8 * DEP_P);
            float m = -INFINITY, l = 0.f;
#pragma unroll
            for (int j = 0; j < 8; j++) {
                m = fmaxf(m, __uint_as_float(lds32(MISC(wmax) + j * 8 + (lane & 1) * 4)));
                l += __uint_as_float(lds32(MISC(wsum) + j * 8 + (lane & 1) * 4));
            }
            if (live && lane < 2) st_rec2(g_rec + OFF_ML + (g8 * 8 + s8) * 2 + lane, m, l, tag);
        } else {
            float c[4][4];
            uint32_t a[4][2][4], bf[5];
            const uint32_t so = lane & 7, sd = so ^ ((mw & 1) << 2);
            const uint32_t ao = smem_base + SM_WO + mw * 4096 + lrow * 128;
            const uint32_t ad = smem_base + SM_WD + mw * WD_BYTES;
            if (live) mbar_wait0(full0 + 8 * (T_WO + mw / 3));
#pragma unroll
            for (int m = 0; m < 4; m++) {
                ldsm4t(a[m][0], ao + (((2 * m + lchk) ^ so) << 4));
                ldsm4t(a[m][1], ao + (((2 * m + lchk) ^ so) << 4) + 2048);
            }
            if (live) mbar_wait0(dep0 + 8 * DEP_O);
            if (live && tid == 160) TRACE_PT(9);
#pragma unroll
            for (int j = 0; j < 4; j++) bf[j] = lds32(MISC(o) + t4 * 4 + j * 16);
#pragma unroll
            for (int m = 0; m < 4; m++) {
                c[m][0] = c[m][1] = c[m][2] = c[m][3] = 0.f;
                mma16816(c[m], a[m][0], bf[0], bf[1]);
            }
#pragma unroll
            for (int m = 0; m < 4; m++) mma16816(c[m], a[m][1], bf[2], bf[3]);
            if (live) mbar_wait0(dep0 + 8 * DEP_H);
            if (live && tid == 160) g_epoch[b] = tag + 1u;
#pragma unroll
            for (int j = 0; j < 5; j++) bf[j] = lds32(MISC(h) + t4 * 4 + j * 16);
            if (live) mbar_wait0(full0 + 8 * (T_WD + mw));
            uint32_t e[2][4];
#pragma unroll
            for (int m = 0; m < 4; m++) ldsm4t(a[m][0], ad + lrow * 128 + (((2 * m + lchk) ^ sd) << 4));
#pragma unroll
            for (int m = 0; m < 4; m++) ldsm4t(a[m][1], ad + lrow * 128 + (((2 * m + lchk) ^ sd) << 4) + 2048);
#pragma unroll
            for (int j = 0; j < 2; j++) ldsm4t(e[j], ad + (so + (so < 4 ? 32 : 24)) * 128 + (((4 * j + (lane >> 3)) ^ sd) << 4));
#pragma unroll
            for (int m = 0; m < 4; m++) mma16816(c[m], a[m][0], bf[0], bf[1]);
#pragma unroll
            for (int m = 0; m < 4; m++) mma16816(c[m], a[m][1], bf[2], bf[3]);
#pragma unroll
            for (int m = 0; m < 4; m++) mma1688(c[m], e[m >> 1][(m & 1) * 2], e[m >> 1][(m & 1) * 2 + 1], bf[4]);
            const float v0 = t4 == 0 ? c[0][0] : t4 == 1 ? c[1][0] : t4 == 2 ? c[2][0] : c[3][0];
            const float v1 = t4 == 0 ? c[0][2] : t4 == 1 ? c[1][2] : t4 == 2 ? c[2][2] : c[3][2];
            const float other = shx((gq & 1) ? v0 : v1, 4);
            const float u0 = (gq & 1) ? other : v0, u1 = (gq & 1) ? v1 : other;
            float4* const acc = g_acc + ACC_IDX(opair);
            const float4 old = atom_add_count(acc, u0, u1, live);
            if (live && tid == 160 + 8 * 32) TRACE_PT(10);
            asm volatile(
                "{\n.reg .pred p;\n"
                "setp.eq.f32 p, %0, 0f43000000;\n"
                "@p st.global.b32 [%2], %1;\n"
                "@p st.global.v4.f32 [%3], {0f00000000, 0f00000000, 0f00000000, 0f00000000};\n}"
                ::"f"(old.z), "r"(pack_bf(old.x + u0, old.y + u1)), "l"(reinterpret_cast<uint32_t*>(out) + opair), "l"(acc) : "memory");
            if (live && tid == 160 + 8 * 32) TRACE_PT(11);
        }
    }
    return;
    }

    {
        const int kvrow = g8 * SK + (SK - WIN) + s8 * 64;
        if (tid == 0) {
            TRACE_PT(13);
#pragma unroll
            for (int j = 0; j < NFIRST; j++) {
                const uint32_t bar = full0 + 8 * j;
                mbar_init(bar, 1);
                asm volatile("fence.mbarrier_init.release.cluster;" ::: "memory");
                mbar_expect_tx(bar, j < T_K ? WQ_BYTES : KV_BYTES);
                if (j < T_K) tma3d(smem_base + SM_WQ + j * WQ_BYTES, &maps.wq, b * 32, j * 144, 0, bar);
                else tma3d(smem_base + (j - T_K) * KV_BYTES, &maps.k, 0, kvrow + (j - T_K) * 512, 0, bar);
                if (j == 0) TRACE_PT(0);
            }
        }
        __syncthreads();
        if (tid == 0) {
            TRACE_PT(15);
            const unsigned long long win_lo = WIN_LO, win_hi = WIN_HI;
            const int pace = PACE, sched0 = SCHED0;
            const uint32_t t0 = (uint32_t)clock64();
            int sched = sched0 << 10;
#pragma unroll 1
            for (int i = NFIRST; i <= T_WD; i++) {
                int c0 = 0, c1, c2 = 0, bytes, mi, dst;
                if (i < T_GU) {
                    mi = (i < T_V) ? 1 : 2; c1 = kvrow + ((i - T_K) & 7) * 512;
                    bytes = KV_BYTES; dst = (i - T_K) * KV_BYTES;
                    if (dst >= KV_WRAP) dst -= KV_WRAP;
                } else if (i < T_WO) {
                    mi = 3; c0 = (b * 36) & ~7; c1 = (i - T_GU) * 144;
                    bytes = 2 * G_BYTES; dst = SM_GU + (i - T_GU) * (2 * G_BYTES);
                } else if (i < T_WD) {
                    mi = 5; c1 = b * 32; c2 = (i - T_WO) * 3;
                    bytes = WO_BYTES; dst = SM_WO + (i - T_WO) * WO_BYTES;
                } else {
                    mi = 6; c1 = b * 36; c2 = i - T_WD;
                    bytes = WD_BYTES; dst = SM_WD + c2 * WD_BYTES;
                }
                const uint32_t bar = full0 + 8 * i;
                if (i == T_V + 3 || i == T_V + 5 || i == T_GU || i == T_WO - 1)
                    mbar_wait0(dep0 + 8 * (i == T_V + 3 ? DEP_QP : i == T_V + 5 ? REL_K : i == T_GU ? DEP_P : REL_V));
                mbar_expect_tx(bar, bytes);
                const int back = (int)(((i < 16) ? win_lo : win_hi) >> ((i & 15) * 4)) & 15;
                sched += bytes * (pace & 0xffff);
                if (back) {
                    if (back + CATCHUP <= i) mbar_wait0(bar - 8 * (back + CATCHUP));
                    unsigned it = 0;
                    while (!mbar_test0(bar - 8 * back) && (int)((uint32_t)clock64() - t0) < (sched >> 10)) {
                        if (++it > SPIN_LIMIT) __trap();
                    }
                }
                tma3d(smem_base + dst, &maps.wq + mi, c0, c1, c2, bar);
                if (mi == 3) tma3d(smem_base + dst + G_BYTES, &maps.wu, c0, c1, c2, bar);
                TRACE_PT(32 + i);
            }
#pragma unroll 1
            for (int j = 1; j < 9; j++) {
                const uint32_t bar = full0 + 8 * (T_WD + j);
                mbar_expect_tx(bar, WD_BYTES);
                tma3d(smem_base + SM_WD + j * WD_BYTES, &maps.wd, 0, b * 36, j, bar);
            }
            TRACE_PT(32 + T_WD + 1);
        }
    }
}

typedef CUresult (*EncodeFn)(CUtensorMap*, CUtensorMapDataType, cuuint32_t, void*, const cuuint64_t*,
                             const cuuint64_t*, const cuuint32_t*, const cuuint32_t*, CUtensorMapInterleave,
                             CUtensorMapSwizzle, CUtensorMapL2promotion, CUtensorMapFloatOOBfill);

void make_map(EncodeFn enc, CUtensorMap* m, const void* base, uint64_t inner, uint64_t rows, uint64_t ngroups,
              uint64_t row_bytes, uint32_t box_inner, uint32_t box_rows, uint32_t box_groups, CUtensorMapSwizzle sw,
              CUtensorMapL2promotion prom) {
    cuuint64_t dims[3] = {inner, rows, ngroups};
    cuuint64_t strides[2] = {row_bytes, inner * 2};
    cuuint32_t box[3] = {box_inner, box_rows, box_groups};
    cuuint32_t es[3] = {1, 1, 1};
    enc(m, CU_TENSOR_MAP_DATA_TYPE_BFLOAT16, 3, const_cast<void*>(base), dims, strides, box, es,
        CU_TENSOR_MAP_INTERLEAVE_NONE, sw, prom, CU_TENSOR_MAP_FLOAT_OOB_FILL_NONE);
}

}

extern "C" void kernel_launch(void* const* d_in, const int* in_sizes, int n_in, void* d_out, int out_size) {
    (void)in_sizes; (void)n_in; (void)out_size;
    static EncodeFn enc = nullptr;
    static void* scratch = nullptr;
    if (!enc) {
        cudaGetSymbolAddress(&scratch, g_scratch);
        cudaDriverEntryPointQueryResult qr;
        void* fn = nullptr;
        cudaGetDriverEntryPoint("cuTensorMapEncodeTiled", &fn, cudaEnableDefault, &qr);
        enc = (EncodeFn)fn;
        cudaFuncSetAttribute(fused_decode_kernel, cudaFuncAttributeMaxDynamicSharedMemorySize, SMEM_BYTES);
    }
    const CUtensorMapL2promotion P128 = CU_TENSOR_MAP_L2_PROMOTION_L2_128B, P256 = CU_TENSOR_MAP_L2_PROMOTION_L2_256B;
#define WQ_PROM P128
#define W_PROM P256
    Maps maps;
    make_map(enc, &maps.wq, d_in[3], 4096, 576, 1, 8192, 32, 144, 1, CU_TENSOR_MAP_SWIZZLE_64B, WQ_PROM);
    make_map(enc, &maps.k, d_in[1], 64, 16ull * SK, 2, 256, 64, 64, 2, CU_TENSOR_MAP_SWIZZLE_128B, P256);
    make_map(enc, &maps.v, d_in[2], 64, 16ull * SK, 2, 256, 64, 64, 2, CU_TENSOR_MAP_SWIZZLE_128B, P256);
    make_map(enc, &maps.wg, d_in[6], 4608, 576, 1, 9216, 40, 144, 1, CU_TENSOR_MAP_SWIZZLE_NONE, P128);
    make_map(enc, &maps.wu, d_in[7], 4608, 576, 1, 9216, 40, 144, 1, CU_TENSOR_MAP_SWIZZLE_NONE, P128);
    make_map(enc, &maps.wo, d_in[4], 64, 4096, 9, 1152, 64, 32, 3, CU_TENSOR_MAP_SWIZZLE_128B, W_PROM);
    make_map(enc, &maps.wd, d_in[8], 64, 4608, 9, 1152, 64, 36, 1, CU_TENSOR_MAP_SWIZZLE_128B, W_PROM);
    fused_decode_kernel<<<NCTA, NTHREADS, SMEM_BYTES, cudaStreamPerThread>>>(
        (const __nv_bfloat16*)d_in[0], (__nv_bfloat16*)d_out, (Scratch*)scratch,
        maps);
}
```

```cpp
#include <cuda_runtime.h>
#include <cuda_bf16.h>
#include <cuda.h>
#include <stdint.h>
#include <stddef.h>

namespace {

constexpr int D_MODEL = 576;
constexpr int SK = 65536;
constexpr int WIN = 4096;
constexpr int NCTA = 128;
constexpr int NXCTA = 4;

constexpr int PACE = 169;
constexpr int SCHED0 = -100;
constexpr int WOFF = 130;
constexpr int STAG = 84, WSTAG = 20;
constexpr int WIN_MIN = 2;
constexpr int WIN_MAX = 6;
constexpr int WLEAD = 6;
constexpr int WESC = 4;
constexpr int XWIN = 6;
constexpr int QTIMER = 2, MLTIMER = 6, OTIMER = 1;

constexpr int ACC_PITCH = 256;
constexpr size_t ACC_ALIGN = 262144;
__host__ __device__ constexpr int acc_idx(int p) { return (p >> 3) * ACC_PITCH + (p & 7); }

constexpr int T_K = 1;
constexpr int T_V = 9;
constexpr int T_GU = 17;
constexpr int T_WO = 21;
constexpr int T_WD = 30;
constexpr int NTILE = 39;
constexpr int XT_WD = 18, XNTILE = 30;

constexpr int KV_BYTES = 16384;
constexpr int KV_WRAP = 13 * KV_BYTES;
constexpr int ST_BYTES = 144 * 64;
constexpr int WO_BYTES = 32 * 384, WD_BYTES = 32 * 128, WB_BYTES = 32 * 1152;
constexpr int SM_WQ = 11 * KV_BYTES;
constexpr int SM_GU = 3 * KV_BYTES;
constexpr int SM_WO = 8 * KV_BYTES;
constexpr int SM_WD = SM_WO + WB_BYTES;
constexpr int SM_XW = 5 * KV_BYTES;
constexpr int SM_END = SM_WQ + 4 * ST_BYTES;
static_assert(SM_GU + 8 * ST_BYTES <= SM_WO && SM_WD + WB_BYTES <= KV_WRAP && SM_XW + 3 * WB_BYTES <= KV_WRAP, "smem plan");

constexpr int NMMA_WARPS = 9;
constexpr int NGATHER_WARPS = 3;
constexpr int NTHREADS = (NMMA_WARPS + NGATHER_WARPS + 1) * 32;
constexpr int P_PITCH = 520;

struct Maps {
    CUtensorMap wq, k, v, wg, wu, wo, wd, xg, xu, xd;
};

constexpr int DEP_X = 0, DEP_O = 1, DEP_Q = 2, DEP_H = 3, DEP_P = 4, REL_K = 5, REL_V = 6, DEP_QP = 7, DEP_GU = 8;
struct SmemMisc {
    unsigned long long full[NTILE];
    unsigned long long dep[11];
    __nv_bfloat16 xn[576];
    __nv_bfloat16 vec[128];
    __nv_bfloat16 q[256];
    __nv_bfloat16 s[2 * 512];
    __nv_bfloat16 p[4 * P_PITCH];
    float red[9 * 32 * 2];
    float wmax[16];
    float wsum[16];
};
constexpr int SMEM_BYTES = SM_END + (int)sizeof(SmemMisc) + 1024;
static_assert(SMEM_BYTES <= 232448, "smem");

constexpr int OFF_Q = 0;
constexpr int OFF_O = NCTA * 8;
constexpr int OFF_ML = OFF_O + 32 * 8 * 64;
constexpr int NREC = OFF_ML + 256;
struct Scratch {
    uint4 rec[NREC];
    unsigned epoch[NCTA];
};
__device__ __align__(128) Scratch g_scratch;
__device__ float4 g_acc_raw[36 * ACC_PITCH + ACC_ALIGN / 16];

constexpr unsigned SPIN_LIMIT = 1u << 22;

__device__ __forceinline__ uint32_t smem_u32(const void* p) { return (uint32_t)__cvta_generic_to_shared(p); }
__device__ __forceinline__ void mbar_init(uint32_t bar, int cnt) {
    asm volatile("mbarrier.init.shared::cta.b64 [%0], %1;" ::"r"(bar), "r"(cnt) : "memory");
}
__device__ __forceinline__ void mbar_expect_tx(uint32_t bar, uint32_t bytes) {
    asm volatile("mbarrier.arrive.expect_tx.shared::cta.b64 _, [%0], %1;" ::"r"(bar), "r"(bytes) : "memory");
}
__device__ __forceinline__ void mbar_arrive(uint32_t bar) {
    asm volatile("mbarrier.arrive.shared::cta.b64 _, [%0];" ::"r"(bar) : "memory");
}
__device__ __forceinline__ uint32_t now_ns() {
    unsigned long long t;
    asm volatile("mov.u64 %0, %globaltimer;" : "=l"(t));
    return (uint32_t)t;
}
__device__ __forceinline__ bool mbar_test0(uint32_t bar) {
    uint32_t ok;
    asm volatile(
        "{\n.reg .pred p;\n"
        "mbarrier.test_wait.parity.shared::cta.b64 p, [%1], 0;\n"
        "selp.u32 %0, 1, 0, p;\n}"
        : "=r"(ok) : "r"(bar) : "memory");
    return ok;
}
__device__ __forceinline__ void pace_wait(uint32_t bar, uint32_t t0, int sched) {
    unsigned it = 0;
    while ((int)(now_ns() - t0) < (sched >> 12) && !mbar_test0(bar)) {
        if (++it > SPIN_LIMIT) __trap();
    }
}
__device__ __forceinline__ void mbar_wait0(uint32_t bar) {
    asm volatile(
        "{\n.reg .pred p;\n.reg .u32 n;\n"
        "mov.u32 n, 0;\n"
        "SPIN:\n"
        "mbarrier.try_wait.parity.shared::cta.b64 p, [%0], 0;\n"
        "@p bra DONE;\n"
        "add.u32 n, n, 1;\n"
        "setp.lt.u32 p, n, 0x400000;\n"
        "@p bra SPIN;\n"
        "trap;\n"
        "DONE:\n}"
        ::"r"(bar) : "memory");
}
__device__ __forceinline__ void tma3d(uint32_t dst, const CUtensorMap* m, int c0, int c1, int c2, uint32_t bar) {
    asm volatile(
        "cp.async.bulk.tensor.3d.shared::cluster.global.mbarrier::complete_tx::bytes [%0], [%1, {%3, %4, %5}], [%2];"
        ::"r"(dst), "l"(m), "r"(bar), "r"(c0), "r"(c1), "r"(c2) : "memory");
}
__device__ __forceinline__ void ldsm4(uint32_t (&r)[4], uint32_t addr) {
    asm volatile("ldmatrix.sync.aligned.m8n8.x4.shared.b16 {%0,%1,%2,%3}, [%4];"
                 : "=r"(r[0]), "=r"(r[1]), "=r"(r[2]), "=r"(r[3]) : "r"(addr) : "memory");
}
__device__ __forceinline__ void ldsm4t(uint32_t (&r)[4], uint32_t addr) {
    asm volatile("ldmatrix.sync.aligned.m8n8.x4.trans.shared.b16 {%0,%1,%2,%3}, [%4];"
                 : "=r"(r[0]), "=r"(r[1]), "=r"(r[2]), "=r"(r[3]) : "r"(addr) : "memory");
}
__device__ __forceinline__ void mma16816(float (&c)[4], const uint32_t (&a)[4], uint32_t b0, uint32_t b1) {
    asm volatile(
        "mma.sync.aligned.m16n8k16.row.col.f32.bf16.bf16.f32 {%0,%1,%2,%3}, {%4,%5,%6,%7}, {%8,%9}, {%0,%1,%2,%3};"
        : "+f"(c[0]), "+f"(c[1]), "+f"(c[2]), "+f"(c[3])
        : "r"(a[0]), "r"(a[1]), "r"(a[2]), "r"(a[3]), "r"(b0), "r"(b1));
}
__device__ __forceinline__ void bar_sync(int id, int n) { asm volatile("bar.sync %0, %1;" ::"r"(id), "r"(n) : "memory"); }

__device__ __forceinline__ unsigned long long pack64(uint32_t lo, uint32_t hi) {
    return ((unsigned long long)hi << 32) | lo;
}
__device__ __forceinline__ void st_rec2(uint4* p, float v0, float v1, uint32_t tag) {
    asm volatile("st.relaxed.gpu.global.v2.b64 [%0], {%1, %2};" ::"l"(p), "l"(pack64(__float_as_uint(v0), tag)),
                 "l"(pack64(__float_as_uint(v1), tag)) : "memory");
}
__device__ __forceinline__ uint4 ld_rec2(const uint4* p) {
    unsigned long long a, b;
    asm volatile("ld.relaxed.gpu.global.v2.b64 {%0, %1}, [%2];" : "=l"(a), "=l"(b) : "l"(p) : "memory");
    return make_uint4((uint32_t)a, (uint32_t)(a >> 32), (uint32_t)b, (uint32_t)(b >> 32));
}
__device__ __forceinline__ float4 atom_add_count(float4* p, float v0, float v1, bool pred) {
    float4 o = make_float4(0.f, 0.f, 0.f, 0.f);
    asm volatile(
        "{\n.reg .pred p;\nsetp.ne.u32 p, %7, 0;\n"
        "@p atom.relaxed.gpu.global.add.v4.f32 {%0,%1,%2,%3}, [%4], {%5,%6,0f3F800000,0f00000000};\n}"
        : "+f"(o.x), "+f"(o.y), "+f"(o.z), "+f"(o.w)
        : "l"(p), "f"(v0), "f"(v1), "r"((uint32_t)pred) : "memory");
    return o;
}
__device__ __forceinline__ float bf16r(float x) { return __bfloat162float(__float2bfloat16_rn(x)); }
__device__ __forceinline__ float bf_lo(uint32_t u) { return __uint_as_float(u << 16); }
__device__ __forceinline__ float bf_hi(uint32_t u) { return __uint_as_float(u & 0xffff0000u); }
__device__ __forceinline__ uint32_t pack_bf(float lo, float hi) {
    __nv_bfloat162 v = __floats2bfloat162_rn(lo, hi);
    return *reinterpret_cast<uint32_t*>(&v);
}
__device__ __forceinline__ uint32_t lds32(uint32_t a) {
    uint32_t v;
    asm volatile("ld.shared.b32 %0, [%1];" : "=r"(v) : "r"(a) : "memory");
    return v;
}
__device__ __forceinline__ float2 lds64f(uint32_t a) {
    float2 v;
    asm volatile("ld.shared.v2.f32 {%0, %1}, [%2];" : "=f"(v.x), "=f"(v.y) : "r"(a) : "memory");
    return v;
}
__device__ __forceinline__ void sts32(uint32_t a, uint32_t v) { asm volatile("st.shared.b32 [%0], %1;" ::"r"(a), "r"(v) : "memory"); }
__device__ __forceinline__ void sts64(uint32_t a, uint32_t x, uint32_t y) {
    asm volatile("st.shared.v2.b32 [%0], {%1, %2};" ::"r"(a), "r"(x), "r"(y) : "memory");
}
__device__ __forceinline__ void sts64f(uint32_t a, float x, float y) {
    asm volatile("st.shared.v2.f32 [%0], {%1, %2};" ::"r"(a), "f"(x), "f"(y) : "memory");
}
__device__ __forceinline__ void sts_bf16(uint32_t a, float v) {
    asm volatile("{\n.reg .b16 h;\ncvt.rn.bf16.f32 h, %1;\nst.shared.b16 [%0], h;\n}" ::"r"(a), "f"(v) : "memory");
}
__device__ __forceinline__ float ex2(float x) {
    float y;
    asm("ex2.approx.ftz.f32 %0, %1;" : "=f"(y) : "f"(x));
    return y;
}
__device__ __forceinline__ float shx(float v, int m) { return __shfl_xor_sync(0xffffffffu, v, m); }
constexpr float L2E = 1.4426950408889634f;
__device__ __forceinline__ float geglu(float g, float u) {
    g = bf16r(g);
    const float k = -2.0f * 0.7978845608028654f * L2E;
    return bf16r(__fdividef(g, 1.0f + ex2(k * (g + 0.044715f * g * g * g)))) * bf16r(u);
}
#define MISC(f) (misc + (uint32_t)offsetof(SmemMisc, f))

__global__ void __launch_bounds__(NTHREADS, 1)
fused_decode_kernel(const __nv_bfloat16* __restrict__ x, __nv_bfloat16* __restrict__ out, Scratch* __restrict__ scr,
                    float4* __restrict__ g_acc, const __grid_constant__ Maps maps) {
    uint4* const g_rec = scr->rec;
    unsigned* const g_epoch = scr->epoch;
    extern __shared__ unsigned char smem_raw[];
    const uint32_t smem_base = (smem_u32(smem_raw) + 1023u) & ~1023u;
    const uint32_t misc = smem_base + SM_END;
    const uint32_t full0 = MISC(full);
    const uint32_t dep0 = MISC(dep);

    const int tid = threadIdx.x;
    const int b = blockIdx.x;
    const int q4 = b >> 2, r4 = b & 3;
    const int g8 = b >> 3, s8 = b & 7;
    const bool xcta = b >= NCTA;
    const int rot = b % 9;

    if (tid == 0) {
        mbar_init(full0, 1);
        asm volatile("fence.mbarrier_init.release.cluster;" ::: "memory");
        if (!xcta) {
            mbar_expect_tx(full0, 4 * ST_BYTES);
            tma3d(smem_base + SM_WQ, &maps.wq, b * 32, 0, 0, full0);
        }
    }
    __syncthreads();

    if (tid >= 32) {
        const int warp = __shfl_sync(0xffffffffu, tid >> 5, 0);
        const int lane = tid & 31;
        uint32_t tag = 0, xs[9];
        if (warp == 1) {
#pragma unroll
            for (int j = 0; j < 9; j++)
                asm volatile("ld.global.nc.u32 %0, [%1];" : "=r"(xs[j]) : "l"(reinterpret_cast<const uint32_t*>(x) + lane + 32 * j));
        }
        if (!xcta && warp != 2) asm volatile("ld.relaxed.gpu.global.u32 %0, [%1];" : "=r"(tag) : "l"(&g_epoch[b]) : "memory");
        if (lane == 0) {
            if (warp >= 2 && warp < 8) asm volatile("prefetch.tensormap [%0];" ::"l"(&maps.wq + (warp - 1) + (xcta ? 3 : 0)) : "memory");
#pragma unroll
            for (int j = 0; j < 4; j++) {
                const int i = warp * 4 - 3 + j;
                mbar_init(full0 + 8 * i, (i < NTILE + DEP_H) ? 1 : (i == NTILE + DEP_H) ? (xcta ? 8 : 1) : (i < NTILE + DEP_QP) ? 8 : 9);
            }
            asm volatile("fence.mbarrier_init.release.cluster;" ::: "memory");
        }
        __syncthreads();

        if (warp <= NGATHER_WARPS) {
            if (warp == 1) {
                float s = 0.f;
#pragma unroll
                for (int j = 0; j < 9; j++) s += bf_lo(xs[j]) + bf_hi(xs[j]);
#pragma unroll
                for (int off = 16; off >= 1; off >>= 1) s += shx(s, off);
                const float mean = s * (1.0f / D_MODEL);
                float v = 0.f;
#pragma unroll
                for (int j = 0; j < 9; j++) {
                    float d0 = bf_lo(xs[j]) - mean, d1 = bf_hi(xs[j]) - mean;
                    v += d0 * d0 + d1 * d1;
                }
#pragma unroll
                for (int off = 16; off >= 1; off >>= 1) v += shx(v, off);
                const float mb = bf16r(mean);
                float den;
                asm("sqrt.approx.f32 %0, %1;" : "=f"(den) : "f"(bf16r(bf16r(v * (1.0f / D_MODEL)) + 1e-5f)));
                const float inv = __fdividef(1.0f, bf16r(den));
#pragma unroll
                for (int j = 0; j < 9; j++)
                    sts32(MISC(xn) + (lane + 32 * j) * 4, pack_bf(bf16r(bf_lo(xs[j]) - mb) * inv, bf16r(bf_hi(xs[j]) - mb) * inv));
                __syncwarp();
                if (lane == 0) mbar_arrive(dep0 + 8 * DEP_X);
            }
            if (xcta) return;
            const int gw = warp - 1;

            float w0 = 0.f, w1 = 0.f, w2 = 0.f, w3 = 0.f;
#pragma unroll 1
            for (uint32_t prog = (0xBA321'00C45'0009Dull >> (20 * gw)) & 0xfffff; prog; prog >>= 4) {
                const bool live = prog & 8;
                const int step = prog & 7;
                if (live) asm volatile("or.b32 %0, %0, 0x80000000;" : "+r"(tag));
                if (step >= 4) {
                    if (live) mbar_wait0(dep0 + 8 * (step == 4 ? DEP_GU : DEP_QP));
                    const uint32_t ra = MISC(red) + lane * 8;
                    float g = 0.f, u = 0.f;
#pragma unroll
                    for (int w = 0; w < 9; w++) {
                        const float2 t = lds64f(ra + w * 256);
                        g += t.x;
                        u += t.y;
                    }
                    if (step == 4) {
                        const float hv = geglu(g, u);
                        if (live) sts_bf16(MISC(vec) + 64 + lane * 2, hv);
                        __syncwarp();
                        if (live && lane == 0) mbar_arrive(dep0 + 8 * DEP_H);
                    } else {
                        const float other = shx((lane & 1) ? g : u, 1);
                        const uint32_t word = (lane & 1) ? pack_bf(other, u) : pack_bf(g, other);
                        const int wi = (lane & 8) + ((lane & 7) >> 1) + (lane & 1) * 4;
                        if (live && lane < 16)
                            asm volatile("st.relaxed.gpu.global.b64 [%0], %1;" ::"l"(reinterpret_cast<uint2*>(g_rec + OFF_Q + b * 8) + wi),
                                         "l"(pack64(word, tag)) : "memory");
                    }
                    continue;
                }
                uint4 r0 = make_uint4(0, 0, 0, 0), r1 = r0, r2 = r0, r3 = r0;
                {
                    int idx, stride;
                    uint32_t wbar;
                    if (step == 1) { idx = OFF_Q + g8 * 64 + (lane & 15); stride = 16; wbar = full0 + 8 * (T_K + QTIMER); }
                    else if (step == 2) { idx = OFF_ML + (g8 * 8 + (lane & 1) * 4) * 2 + (q4 & 1); stride = 2; wbar = full0 + 8 * (T_V + MLTIMER); }
                    else { idx = OFF_O + (q4 * 8 + (lane & 1) * 4) * 64 + r4 * 16 + (lane >> 1); stride = 64; wbar = full0 + 8 * (T_GU + OTIMER); }
                    const uint32_t want = live ? tag : 0u;
                    if (live) mbar_wait0(wbar);
                    const uint4* src = g_rec + idx;
                    unsigned it = 0;
                    while (true) {
                        if (r0.y != want || r0.w != want) r0 = ld_rec2(src);
                        if (r1.y != want || r1.w != want) r1 = ld_rec2(src + stride);
                        if (r2.y != want || r2.w != want) r2 = ld_rec2(src + 2 * stride);
                        if (r3.y != want || r3.w != want) r3 = ld_rec2(src + 3 * stride);
                        const uint32_t bad = ((r0.y ^ want) | (r0.w ^ want) | (r1.y ^ want)) | ((r1.w ^ want) | (r2.y ^ want) | (r2.w ^ want)) |
                                             ((r3.y ^ want) | (r3.w ^ want));
                        if (bad == 0) break;
                        if (++it > SPIN_LIMIT) __trap();
                    }
                    __syncwarp();
                }
                const float a0 = __uint_as_float(r0.x), a1 = __uint_as_float(r1.x), a2 = __uint_as_float(r2.x), a3 = __uint_as_float(r3.x);
                const float b0 = __uint_as_float(r0.z), b1 = __uint_as_float(r1.z), b2 = __uint_as_float(r2.z), b3 = __uint_as_float(r3.z);
                if (step == 2) {
                    float mx = fmaxf(fmaxf(a0, a1), fmaxf(a2, a3));
                    mx = fmaxf(mx, shx(mx, 1));
                    w0 = ex2((a0 - mx) * L2E); w1 = ex2((a1 - mx) * L2E); w2 = ex2((a2 - mx) * L2E); w3 = ex2((a3 - mx) * L2E);
                    float L = w0 * b0 + w1 * b1 + w2 * b2 + w3 * b3;
                    L += shx(L, 1);
                    const float inv = __fdividef(1.0f, L);
                    w0 *= inv; w1 *= inv; w2 *= inv; w3 *= inv;
                } else if (step == 3) {
                    const float u = w0 * a0 + w1 * a1 + w2 * a2 + w3 * a3;
                    const float v = w0 * b0 + w1 * b1 + w2 * b2 + w3 * b3;
                    const float tot = ((lane & 1) ? v : u) + shx((lane & 1) ? u : v, 1);
                    if (live) sts_bf16(MISC(vec) + ((lane & 16) + ((lane >> 1) & 7) + (lane & 1) * 8) * 2, tot);
                    __syncwarp();
                    if (live && lane == 0) mbar_arrive(dep0 + 8 * DEP_O);
                } else {
                    const uint32_t qa = MISC(q) + (lane & 15) * 8;
                    if (live) {
                        sts64(qa, r0.x, r0.z);
                        sts64(qa + 128, r1.x, r1.z);
                        sts64(qa + 256, r2.x, r2.z);
                        sts64(qa + 384, r3.x, r3.z);
                    }
                    __syncwarp();
                    if (live && lane == 0) mbar_arrive(dep0 + 8 * DEP_Q);
                }
            }
            return;
        }

        const int mw = warp - 1 - NGATHER_WARPS;
        const int gq = lane >> 2, t4 = lane & 3;
        const int lrow = (lane & 7) + ((lane >> 4) << 3);
        const int lchk = (lane >> 3) & 1;
        uint4* const rec_o = g_rec + OFF_O + ((g8 * 2 + (t4 & 1)) * 8 + s8) * 64 + mw * 8 + gq;

        float xg0 = 0.f, xg1 = 0.f;
#pragma unroll 1
        for (uint32_t prog = xcta ? (mw < 8 ? 0xECCu : 0xEu) : (mw < 8 ? 0xEDCBA90u : 0xEDF90u) | (mw < 7 ? mw + 1 : 1); prog; prog >>= 4) {
            const bool live = prog & 8;
            const int sec = prog & 7;
            if (live) asm volatile("or.b32 %0, %0, 0x80000000;" : "+r"(tag));
            if (sec == 1 || sec == 5) {
                const bool gu = sec == 5;
                float acc[4][4];
#pragma unroll
                for (int c = 0; c < 4; c++) acc[c][0] = acc[c][1] = acc[c][2] = acc[c][3] = 0.f;
                const int sw = (lane >> 1) & 3;
                uint32_t base = smem_base + (mw * 16 + lrow) * 64 + (gu ? SM_GU + lchk * ST_BYTES : SM_WQ);
                const uint32_t o0 = ((gu ? 0 : lchk) ^ sw) << 4, o1 = ((gu ? 1 : 2 + lchk) ^ sw) << 4;
                uint32_t baddr = MISC(xn) + mw * 32 + t4 * 4;
                uint32_t bar = full0 + (gu ? 8 * T_GU : 0);
                if (live) mbar_wait0(dep0 + 8 * DEP_X);
#pragma unroll 1
                for (int i = live ? 0 : 3; i < 4; i++) {
                    const uint32_t b0 = lds32(baddr), b1 = lds32(baddr + 16);
                    baddr += 288;
                    if (live) mbar_wait0(bar);
                    bar += gu ? 8 : 0;
                    uint32_t a[4][4];
                    ldsm4t(a[0], base + o0);
                    ldsm4t(a[1], base + o1);
                    if (gu) {
                        ldsm4t(a[2], base + (o0 ^ 32));
                        ldsm4t(a[3], base + (o1 ^ 32));
                    }
                    mma16816(acc[0], a[0], b0, b1);
                    mma16816(acc[1], a[1], b0, b1);
                    if (gu) {
                        mma16816(acc[2], a[2], b0, b1);
                        mma16816(acc[3], a[3], b0, b1);
                    }
                    base += gu ? 2 * ST_BYTES : ST_BYTES;
                }
                sts64f(MISC(red) + (mw * 32 + t4 * 8 + gq) * 8,
                       t4 == 0 ? acc[0][0] : t4 == 1 ? acc[1][0] : t4 == 2 ? acc[2][0] : acc[3][0],
                       t4 == 0 ? acc[0][2] : t4 == 1 ? acc[1][2] : t4 == 2 ? acc[2][2] : acc[3][2]);
                __syncwarp();
                if (live && lane == 0) mbar_arrive(dep0 + 8 * (gu ? DEP_GU : DEP_QP));
            } else if (sec == 2) {
                if (live) mbar_wait0(dep0 + 8 * DEP_Q);
                uint32_t qb[16];
#pragma unroll
                for (int j = 0; j < 16; j++) qb[j] = lds32(MISC(q) + (gq & 1) * 256 + t4 * 4 + j * 16);
                const int krow = (mw & 3) * 16 + (lane & 15);
                float m = -INFINITY;
#pragma unroll 1
                for (int i = live ? 0 : 3; i < 4; i++) {
                    const int kt = (mw >> 2) + 2 * i;
                    const uint32_t base = smem_base + kt * KV_BYTES + krow * 128;
                    if (live) mbar_wait0(full0 + 8 * (T_K + kt));
                    float c0[4] = {0.f, 0.f, 0.f, 0.f}, c1[4] = {0.f, 0.f, 0.f, 0.f};
#pragma unroll
                    for (int ks = 0; ks < 4; ks++) {
                        uint32_t a0[4], a1[4];
                        const uint32_t sw = ((ks * 2 + (lane >> 4)) ^ (lane & 7)) << 4;
                        ldsm4(a0, base + sw);
                        ldsm4(a1, base + 8192 + sw);
                        mma16816(c0, a0, qb[2 * ks], qb[2 * ks + 1]);
                        mma16816(c1, a1, qb[8 + 2 * ks], qb[8 + 2 * ks + 1]);
                    }
                    __syncwarp();
                    if (i == 1 && lane == 0) mbar_arrive(dep0 + 8 * REL_K);
                    const float lo = (t4 & 1) ? c0[1] + c1[1] : c0[0] + c1[0];
                    const float hi = (t4 & 1) ? c0[3] + c1[3] : c0[2] + c1[2];
                    const float sc = bf16r(bf16r((t4 & 2) ? hi : lo) * 0.08838834764831845f);
                    m = fmaxf(m, sc);
                    sts_bf16(MISC(s) + ((t4 & 1) * 512 + kt * 64 + (mw & 3) * 16 + gq + (t4 & 2) * 4) * 2, sc);
                }
#pragma unroll
                for (int off = 2; off <= 16; off <<= 1) m = fmaxf(m, shx(m, off));
                if (lane < 2) sts32(MISC(wmax) + mw * 8 + lane * 4, __float_as_uint(m));
            } else if (sec == 3) {
                if (live) bar_sync(1, 256);
                float m0 = -INFINITY, m1 = -INFINITY;
#pragma unroll
                for (int j = 0; j < 8; j++) {
                    m0 = fmaxf(m0, __uint_as_float(lds32(MISC(wmax) + j * 8)));
                    m1 = fmaxf(m1, __uint_as_float(lds32(MISC(wmax) + j * 8 + 4)));
                }
                const int kp = mw * 32 + lane;
                const uint32_t s0 = lds32(MISC(s) + kp * 4);
                const uint32_t s1 = lds32(MISC(s) + 1024 + kp * 4);
                const float p00 = ex2((bf_lo(s0) - m0) * L2E), p01 = ex2((bf_hi(s0) - m0) * L2E);
                const float p10 = ex2((bf_lo(s1) - m1) * L2E), p11 = ex2((bf_hi(s1) - m1) * L2E);
                const uint32_t h0 = pack_bf(p00, p01), h1 = pack_bf(p10, p11);
                const uint32_t pa = MISC(p) + kp * 4;
                sts32(pa, h0);
                sts32(pa + P_PITCH * 2, pack_bf(p00 - bf_lo(h0), p01 - bf_hi(h0)));
                sts32(pa + P_PITCH * 4, h1);
                sts32(pa + P_PITCH * 6, pack_bf(p10 - bf_lo(h1), p11 - bf_hi(h1)));
                const float l0 = p00 + p01, l1 = p10 + p11;
                float l = ((lane & 1) ? l1 : l0) + shx((lane & 1) ? l0 : l1, 1);
#pragma unroll
                for (int off = 2; off <= 16; off <<= 1) l += shx(l, off);
                if (lane < 2) sts32(MISC(wsum) + mw * 8 + lane * 4, __float_as_uint(l));
                __syncwarp();
                if (live && lane == 0) mbar_arrive(dep0 + 8 * DEP_P);
            } else if (sec == 4) {
                const bool up = xcta && prog < 0x100u;
                const uint32_t a_off = smem_base + lrow * 128 + ((((mw & 3) * 2 + lchk) ^ (lane & 7)) << 4) + (mw & 4) * 2048;
                int taddr = (xcta ? (up ? 9 : 0) : 8) * KV_BYTES;
                uint32_t baddr = t4 * 4 + (xcta ? MISC(xn) : MISC(p) + (gq & 3) * (P_PITCH * 2));
                const uint32_t bar = full0 + 8 * (xcta ? (up ? 9 : 0) : T_V);
                if (live) mbar_wait0(dep0 + 8 * (xcta ? DEP_X : DEP_P));
                float c0[4] = {0.f, 0.f, 0.f, 0.f}, c1[4] = {0.f, 0.f, 0.f, 0.f};
#pragma unroll 1
                for (int i = live ? 0 : 7; i < (xcta ? 9 : 8); i++) {
                    const uint32_t base = a_off + taddr;
                    taddr += KV_BYTES;
                    if (taddr >= KV_WRAP) taddr -= KV_WRAP;
                    uint32_t bf[8];
#pragma unroll
                    for (int j = 0; j < 8; j++) bf[j] = lds32(baddr + j * 16);
                    baddr += 128;
                    if (live) mbar_wait0(bar + 8 * i);
                    uint32_t a0[4], a1[4], a2[4], a3[4];
                    ldsm4t(a0, base);
                    ldsm4t(a1, base + 2048);
                    ldsm4t(a2, base + 4096);
                    ldsm4t(a3, base + 6144);
                    mma16816(c0, a0, bf[0], bf[1]);
                    mma16816(c1, a1, bf[2], bf[3]);
                    mma16816(c0, a2, bf[4], bf[5]);
                    mma16816(c1, a3, bf[6], bf[7]);
                    __syncwarp();
                    if (i == 4 && lane == 0) mbar_arrive(dep0 + 8 * (up ? REL_K : REL_V));
                }
                if (!xcta) {
                    if (live && t4 < 2) st_rec2(rec_o, (c0[0] + c1[0]) + (c0[1] + c1[1]), (c0[2] + c1[2]) + (c0[3] + c1[3]), tag);
                } else if (!up) {
                    xg0 = c0[0] + c1[0];
                    xg1 = c0[2] + c1[2];
                } else {
                    sts_bf16(MISC(vec) + (mw * 16 + gq + (t4 & 1) * 8) * 2, geglu((t4 & 1) ? xg1 : xg0, (t4 & 1) ? c0[2] + c1[2] : c0[0] + c1[0]));
                    __syncwarp();
                    if (lane == 0) mbar_arrive(dep0 + 8 * DEP_H);
                }
            } else if (sec == 7) {
                if (live) mbar_wait0(dep0 + 8 * DEP_P);
                float m = -INFINITY, l = 0.f;
#pragma unroll
                for (int j = 0; j < 8; j++) {
                    m = fmaxf(m, __uint_as_float(lds32(MISC(wmax) + j * 8 + (lane & 1) * 4)));
                    l += __uint_as_float(lds32(MISC(wsum) + j * 8 + (lane & 1) * 4));
                }
                if (live && lane < 2) st_rec2(g_rec + OFF_ML + (g8 * 8 + s8) * 2 + lane, m, l, tag);
            } else {
                const int ocol = mw * 64 + t4 * 16 + gq;
                float c[4][4], xr0 = 0.f, xr1 = 0.f;
                if (b == NCTA) {
                    xr0 = __bfloat162float(x[ocol]);
                    xr1 = __bfloat162float(x[ocol + 8]);
                }
#pragma unroll
                for (int m = 0; m < 4; m++) {
                    c[m][0] = xr0;
                    c[m][2] = xr1;
                    c[m][1] = c[m][3] = 0.f;
                }
                const uint32_t aw = smem_base + mw * 4096 + lrow * 128 + ((lchk ^ (lane & 7)) << 4);
#pragma unroll 1
                for (int kb = live ? 0 : 1; kb < (xcta ? 4 : 2); kb++) {
                    if (live) mbar_wait0(dep0 + 8 * ((kb || xcta) ? DEP_H : DEP_O));
                    uint32_t bf[4], a[4][2][4];
#pragma unroll
                    for (int j = 0; j < 4; j++) bf[j] = lds32(MISC(vec) + kb * 64 + t4 * 4 + j * 16);
                    uint32_t ad0 = aw + (kb == 3 ? 0 : (xcta ? SM_XW : SM_WO) + kb * WB_BYTES);
                    uint32_t ad1 = ad0 ^ 32, ad2 = ad0 ^ 64, ad3 = ad0 ^ 96;
                    const uint32_t wbar = full0 + 8 * (xcta ? XT_WD + kb * 3 + mw / 3 : T_WO + kb * (T_WD - T_WO) + (mw >= rot ? mw - rot : mw + 9 - rot));
                    asm volatile(
                        "{\n.reg .pred p;\n.reg .u32 n;\n"
                        "setp.eq.u32 p, %37, 0;\n"
                        "mov.u32 n, 0;\n"
                        "@p bra WGO;\n"
                        "WSPIN:\n"
                        "mbarrier.try_wait.parity.shared::cta.b64 p, [%36], 0;\n"
                        "@p bra WGO;\n"
                        "add.u32 n, n, 1;\n"
                        "setp.lt.u32 p, n, 0x400000;\n"
                        "@p bra WSPIN;\n"
                        "trap;\n"
                        "WGO:\n"
                        "ldmatrix.sync.aligned.m8n8.x4.trans.shared.b16 {%0,%1,%2,%3}, [%32];\n"
                        "ldmatrix.sync.aligned.m8n8.x4.trans.shared.b16 {%4,%5,%6,%7}, [%33];\n"
                        "ldmatrix.sync.aligned.m8n8.x4.trans.shared.b16 {%8,%9,%10,%11}, [%34];\n"
                        "ldmatrix.sync.aligned.m8n8.x4.trans.shared.b16 {%12,%13,%14,%15}, [%35];\n"
                        "ldmatrix.sync.aligned.m8n8.x4.trans.shared.b16 {%16,%17,%18,%19}, [%32+2048];\n"
                        "ldmatrix.sync.aligned.m8n8.x4.trans.shared.b16 {%20,%21,%22,%23}, [%33+2048];\n"
                        "ldmatrix.sync.aligned.m8n8.x4.trans.shared.b16 {%24,%25,%26,%27}, [%34+2048];\n"
                        "ldmatrix.sync.aligned.m8n8.x4.trans.shared.b16 {%28,%29,%30,%31}, [%35+2048];\n}"
                        : "=r"(a[0][0][0]), "=r"(a[0][0][1]), "=r"(a[0][0][2]), "=r"(a[0][0][3]),
                          "=r"(a[1][0][0]), "=r"(a[1][0][1]), "=r"(a[1][0][2]), "=r"(a[1][0][3]),
                          "=r"(a[2][0][0]), "=r"(a[2][0][1]), "=r"(a[2][0][2]), "=r"(a[2][0][3]),
                          "=r"(a[3][0][0]), "=r"(a[3][0][1]), "=r"(a[3][0][2]), "=r"(a[3][0][3]),
                          "=r"(a[0][1][0]), "=r"(a[0][1][1]), "=r"(a[0][1][2]), "=r"(a[0][1][3]),
                          "=r"(a[1][1][0]), "=r"(a[1][1][1]), "=r"(a[1][1][2]), "=r"(a[1][1][3]),
                          "=r"(a[2][1][0]), "=r"(a[2][1][1]), "=r"(a[2][1][2]), "=r"(a[2][1][3]),
                          "=r"(a[3][1][0]), "=r"(a[3][1][1]), "=r"(a[3][1][2]), "=r"(a[3][1][3])
                        : "r"(ad0), "r"(ad1), "r"(ad2), "r"(ad3), "r"(wbar), "r"((uint32_t)live)
                        : "memory");
#pragma unroll
                    for (int m = 0; m < 4; m++) mma16816(c[m], a[m][0], bf[0], bf[1]);
#pragma unroll
                    for (int m = 0; m < 4; m++) mma16816(c[m], a[m][1], bf[2], bf[3]);
                }
                const float v0 = t4 == 0 ? c[0][0] : t4 == 1 ? c[1][0] : t4 == 2 ? c[2][0] : c[3][0];
                const float v1 = t4 == 0 ? c[0][2] : t4 == 1 ? c[1][2] : t4 == 2 ? c[2][2] : c[3][2];
                float4* const acc = g_acc + acc_idx(mw * 32 + t4 * 8 + gq);
                const float4 old = atom_add_count(acc, v0, v1, live);
                asm volatile(
                    "{\n.reg .pred p;\n.reg .b16 lo, hi;\n"
                    "setp.eq.f32 p, %0, 0f43030000;\n"
                    "mov.b32 {lo, hi}, %1;\n"
                    "@p st.global.b16 [%2], lo;\n"
                    "@p st.global.b16 [%2+16], hi;\n"
                    "@p st.global.v4.f32 [%3], {0f00000000, 0f00000000, 0f00000000, 0f00000000};\n}"
                    ::"f"(old.z), "r"(pack_bf(old.x + v0, old.y + v1)), "l"(out + ocol), "l"(acc) : "memory");
                if (live && tid == 32 * (NGATHER_WARPS + 1) && !xcta) g_epoch[b] = tag + 1u;
            }
        }
        return;
    }

    {
        const int kvrow = g8 * SK + (SK - WIN) + s8 * 64;
        __syncthreads();
        if (tid == 0 && xcta) {
#pragma unroll 1
            for (int i = 0; i < XNTILE; i++) {
                const uint32_t bar = full0 + 8 * i;
                if (i == 13 || i == XT_WD || i == XT_WD + 9) mbar_wait0(dep0 + 8 * (i == 13 ? REL_V : i == XT_WD ? REL_K : DEP_H));
                mbar_expect_tx(bar, i < XT_WD ? KV_BYTES : WO_BYTES);
                if (i >= XWIN) mbar_wait0(bar - 8 * XWIN);
                const int j = i - XT_WD, kb = j / 3;
                if (i < XT_WD) tma3d(smem_base + (i >= 13 ? i - 13 : i) * KV_BYTES, i < 9 ? &maps.xg : &maps.xu, 0, (i < 9 ? i : i - 9) * 64, (b - 96) * 2, bar);
                else tma3d(smem_base + (kb == 3 ? (j - 9) * WO_BYTES : SM_XW + j * WO_BYTES), &maps.xd, 0, (b - 96) * 128 + kb * 32, (j - kb * 3) * 3, bar);
            }
        } else if (tid == 0) {
            const uint32_t t0 = now_ns();
            int sched = (SCHED0 + s8 * STAG - (7 * STAG) / 2) * 4096;
#pragma unroll 1
            for (int i = 1; i < T_WO; i++) {
                const bool gu = i >= T_GU;
                const int bytes = gu ? 2 * ST_BYTES : KV_BYTES;
                const int c0 = gu ? b * 32 : 0;
                const int c1 = gu ? (i - T_GU) * 144 : kvrow + ((i - T_K) & 7) * 512;
                const int dst = gu ? SM_GU + (i - T_GU) * (2 * ST_BYTES) : (i - T_K - (i - T_K >= 13 ? 13 : 0)) * KV_BYTES;
                const uint32_t bar = full0 + 8 * i;
                if (i == T_V + 3 || i == T_V + 5 || i == T_GU || i == T_WO - 1)
                    mbar_wait0(dep0 + 8 * (i == T_V + 3 ? DEP_QP : i == T_V + 5 ? REL_K : i == T_GU ? DEP_P : REL_V));
                mbar_expect_tx(bar, bytes);
                sched += bytes * PACE;
                if (i >= WIN_MAX) mbar_wait0(bar - 8 * WIN_MAX);
                pace_wait(i >= WIN_MIN ? bar - 8 * WIN_MIN : full0, t0, sched);
                tma3d(smem_base + dst, gu ? &maps.wg : i < T_V ? &maps.k : &maps.v, c0, c1, 0, bar);
                if (gu) tma3d(smem_base + dst + ST_BYTES, &maps.wu, c0, c1, 0, bar);
            }
            sched += (WOFF + s8 * (WSTAG - STAG) + (7 * STAG) / 2) * 4096;
            unsigned long long hist = 0x0101010101010101ull * (T_WO - 1);
#pragma unroll 1
            for (int j = 0; j < 18; j++) {
                const int jj = j - WLEAD;
                const bool d = j >= 18 - WLEAD || (jj >= 0 && !(jj & 1));
                const int r = jj < 0 ? j : j >= 18 - WLEAD ? j - 9 : d ? jj >> 1 : WLEAD + (jj >> 1);
                const int idx = (d ? T_WD : T_WO) + r;
                const int cs = r + rot - (r + rot >= 9 ? 9 : 0);
                mbar_expect_tx(full0 + 8 * idx, WD_BYTES);
                sched += PACE * 4096;
                pace_wait(full0 + 8 * (int)((hist >> (8 * (WESC - 1))) & 255), t0, sched);
                hist = (hist << 8) | idx;
                tma3d(smem_base + (d ? SM_WD : SM_WO) + cs * WD_BYTES, d ? &maps.wd : &maps.wo, 0, b * 32, cs, full0 + 8 * idx);
            }
        }
    }
}

typedef CUresult (*EncodeFn)(CUtensorMap*, CUtensorMapDataType, cuuint32_t, void*, const cuuint64_t*,
                             const cuuint64_t*, const cuuint32_t*, const cuuint32_t*, CUtensorMapInterleave,
                             CUtensorMapSwizzle, CUtensorMapL2promotion, CUtensorMapFloatOOBfill);

void make_map(EncodeFn enc, CUtensorMap* m, const void* base, uint64_t inner, uint64_t rows, uint64_t ngroups,
              uint64_t row_bytes, uint32_t box_inner, uint32_t box_rows, uint32_t box_groups, CUtensorMapSwizzle sw,
              uint64_t group_bytes = 0) {
    cuuint64_t dims[3] = {inner, rows, ngroups};
    cuuint64_t strides[2] = {row_bytes, group_bytes ? group_bytes : inner * 2};
    cuuint32_t box[3] = {box_inner, box_rows, box_groups};
    cuuint32_t es[3] = {1, 1, 1};
    enc(m, CU_TENSOR_MAP_DATA_TYPE_BFLOAT16, 3, const_cast<void*>(base), dims, strides, box, es,
        CU_TENSOR_MAP_INTERLEAVE_NONE, sw, CU_TENSOR_MAP_L2_PROMOTION_L2_256B, CU_TENSOR_MAP_FLOAT_OOB_FILL_NONE);
}

}

extern "C" void kernel_launch(void* const* d_in, const int* in_sizes, int n_in, void* d_out, int out_size) {
    (void)in_sizes; (void)n_in; (void)out_size;
    static EncodeFn enc = nullptr;
    static void* scratch = nullptr;
    static void* acc = nullptr;
    if (!enc) {
        cudaGetSymbolAddress(&scratch, g_scratch);
        cudaGetSymbolAddress(&acc, g_acc_raw);
        acc = (void*)(((uintptr_t)acc + ACC_ALIGN - 1) / ACC_ALIGN * ACC_ALIGN);
        cudaDriverEntryPointQueryResult qr;
        void* fn = nullptr;
        cudaGetDriverEntryPoint("cuTensorMapEncodeTiled", &fn, cudaEnableDefault, &qr);
        enc = (EncodeFn)fn;
        cudaFuncSetAttribute(fused_decode_kernel, cudaFuncAttributeMaxDynamicSharedMemorySize, SMEM_BYTES);
    }
    Maps maps;
    make_map(enc, &maps.wq, d_in[3], 4096, 144, 4, 8192, 32, 144, 4, CU_TENSOR_MAP_SWIZZLE_64B, 144 * 8192);
    make_map(enc, &maps.k, d_in[1], 64, 16ull * SK, 2, 256, 64, 64, 2, CU_TENSOR_MAP_SWIZZLE_128B);
    make_map(enc, &maps.v, d_in[2], 64, 16ull * SK, 2, 256, 64, 64, 2, CU_TENSOR_MAP_SWIZZLE_128B);
    make_map(enc, &maps.wg, d_in[6], 4608, 576, 1, 9216, 32, 144, 1, CU_TENSOR_MAP_SWIZZLE_64B);
    make_map(enc, &maps.xg, d_in[6], 64, 576, 72, 9216, 64, 64, 2, CU_TENSOR_MAP_SWIZZLE_128B);
    make_map(enc, &maps.wu, d_in[7], 4608, 576, 1, 9216, 32, 144, 1, CU_TENSOR_MAP_SWIZZLE_64B);
    make_map(enc, &maps.xu, d_in[7], 64, 576, 72, 9216, 64, 64, 2, CU_TENSOR_MAP_SWIZZLE_128B);
    make_map(enc, &maps.wo, d_in[4], 64, 4096, 9, 1152, 64, 32, 1, CU_TENSOR_MAP_SWIZZLE_128B);
    make_map(enc, &maps.wd, d_in[8], 64, 4608, 9, 1152, 64, 32, 1, CU_TENSOR_MAP_SWIZZLE_128B);
    make_map(enc, &maps.xd, d_in[8], 64, 4608, 9, 1152, 64, 32, 3, CU_TENSOR_MAP_SWIZZLE_128B);
    cudaLaunchConfig_t cfg = {};
    cfg.gridDim = dim3(NCTA + NXCTA);
    cfg.blockDim = dim3(NTHREADS);
    cfg.dynamicSmemBytes = SMEM_BYTES;
    cfg.stream = cudaStreamPerThread;
    cudaLaunchAttribute attr;
    attr.id = cudaLaunchAttributeCooperative;
    attr.val.cooperative = 1;
    cfg.attrs = &attr;
    cfg.numAttrs = 1;
    cudaLaunchKernelEx(&cfg, fused_decode_kernel, (const __nv_bfloat16*)d_in[0], (__nv_bfloat16*)d_out, (Scratch*)scratch,
                       (float4*)acc, maps);
}
```
